```python
import torch

def _softmax(x, axis=-1):
    return torch.softmax(x, dim=axis)
def _gelu(x):
    return torch.nn.functional.gelu(x, approximate="tanh")
def _silu(x):
    return torch.nn.functional.silu(x)
def _sigmoid(x):
    return torch.sigmoid(x)
def _layernorm(x, axis=-1, eps=1e-5):
    m = x.mean(dim=axis, keepdim=True)
    v = x.var(dim=axis, keepdim=True, unbiased=False)
    return (x - m) / torch.sqrt(v + eps)
def _scatter_add(tgt, idx, src, axis=0):
    return tgt.clone().index_add_(axis, idx, src)
def _segment_sum(src, seg, n):
    out = torch.zeros((n,) + src.shape[1:], dtype=src.dtype)
    return out.index_add_(0, seg, src)
def _pad(x, pw):
    flat = tuple(v for pair in reversed(pw) for v in pair)
    return torch.nn.functional.pad(x, flat)

kernel_name = 'interleave_layers__ssm_conv_h3__glu_gated_glu__prompt'

def setup_inputs():

    _w = (lambda a: (lambda t: t.to(torch.bfloat16) if t.is_floating_point() else t)(torch.as_tensor(a)))
    def _A_setup():
        B, S, D = 1, 2048, 512
        ks = 4
        return {
            "q": _w((lambda *s: torch.randn(*s, dtype=torch.bfloat16) * 0.05)(B, S, D)),
            "k": _w((lambda *s: torch.randn(*s, dtype=torch.bfloat16) * 0.4)(B, S, D)),
            "v": _w((lambda *s: torch.randn(*s, dtype=torch.bfloat16) * 0.4)(B, S, D)),
            "shift_k": _w((lambda *s: torch.randn(*s, dtype=torch.bfloat16) * 0.4)(D, ks) * 0.5),
            "ssm_k": _w((lambda *s: torch.randn(*s, dtype=torch.bfloat16) * 0.4)(D, S) * (1.0 / S ** 0.5)),
            "ssm_D": _w((lambda *s: torch.randn(*s, dtype=torch.bfloat16) * 0.4)(D)),
        }
    _A_in = _A_setup()

    def _B_setup():
        B, S, D, F = 1, 2048, 512, 1792
        return {
            "x": _w((lambda *s: torch.randn(*s, dtype=torch.bfloat16) * 0.05)(B, S, D)),
            "w_gate": _w((lambda *s: torch.randn(*s, dtype=torch.bfloat16) * 0.05)(D, F)),
            "w_up": _w((lambda *s: torch.randn(*s, dtype=torch.bfloat16) * 0.05)(D, F)),
            "w_down": _w((lambda *s: torch.randn(*s, dtype=torch.bfloat16) * 0.05)(F, D)),
        }
    _B_in = _B_setup()

    return {
        "A_q": _A_in["q"],
        "A_k": _A_in["k"],
        "A_v": _A_in["v"],
        "A_shift_k": _A_in["shift_k"],
        "A_ssm_k": _A_in["ssm_k"],
        "A_ssm_D": _A_in["ssm_D"],
        "B_x": _B_in["x"],
        "B_w_gate": _B_in["w_gate"],
        "B_w_up": _B_in["w_up"],
        "B_w_down": _B_in["w_down"],
    }

def reference(A_q, A_k, A_v, A_shift_k, A_ssm_k, A_ssm_D, B_x, B_w_gate, B_w_up, B_w_down):
    def _A_ref(q, k, v, shift_k, ssm_k, ssm_D):
        B, S, D = q.shape
        ks = shift_k.shape[-1]
        k_pad = _pad(k, ((0, 0), (ks - 1, 0), (0, 0)))
        k_shift = torch.zeros_like(k)
        for t in range(ks):
            k_shift = k_shift + k_pad[:, t:t + S, :] * shift_k[:, ks - 1 - t][None, None, :]
        kv = k_shift * v
        L = 2 * S
        kv_pad = _pad(kv, ((0, 0), (0, S), (0, 0)))
        kf_pad = _pad(ssm_k, ((0, 0), (0, S)))
        kv_f = (lambda x, axes=(-2,-1): torch.fft.rfft2(x.float(), dim=axes))(kv_pad[:, None, :, :], axes=(1, 2))
        kf_f = (lambda x, axes=(-2,-1): torch.fft.rfft2(x.float(), dim=axes))(kf_pad[:, None, :], axes=(1, 2))
        kf_f = (lambda x, *d: x.permute(*d))(kf_f, 1, 2, 0)
        y_f = kv_f * kf_f[None, :, :, :]
        y = (lambda x, s, axes=(-2,-1): torch.fft.irfft2(x, s=s, dim=axes).to(torch.bfloat16))(y_f, (1, L), axes=(1, 2))[:, 0, :S, :]
        y = y + kv * ssm_D[None, None, :]
        return q * y

    def _B_ref(x, w_gate, w_up, w_down):
        g = torch.einsum("bsd,df->bsf", x, w_gate)
        u = torch.einsum("bsd,df->bsf", x, w_up)
        h = _sigmoid(g) * u
        return torch.einsum("bsf,fd->bsd", h, w_down)

    x = A_q
    x = x + _A_ref(_layernorm(x, axis=-1), A_k, A_v, A_shift_k, A_ssm_k, A_ssm_D)
    x = x + _B_ref(_layernorm(x, axis=-1), B_w_gate, B_w_up, B_w_down)
    x = x + _A_ref(_layernorm(x, axis=-1), A_k, A_v, A_shift_k, A_ssm_k, A_ssm_D)
    x = x + _B_ref(_layernorm(x, axis=-1), B_w_gate, B_w_up, B_w_down)
    return x
```

```cpp
#include <cuda_runtime.h>
#include <cuda.h>
#include <cuda_bf16.h>
#include <stdint.h>

namespace {

__device__ __align__(1024) uint32_t g_y[256 * 2048];
__device__ __align__(1024) __nv_bfloat16 g_xn[2048 * 512];
__device__ __align__(1024) __nv_bfloat16 g_wp[8 * 512 * 64];
__device__ __align__(1024) __nv_bfloat16 g_f[3 * 2048 * 512];
constexpr int CNT_Y = 0, CNT_W = 2, CNT_EPOCH = 3, CNT_X = 4, CNT_Z = 36, CNT_DONE = 52, CNT_P = 53, CNT_N = 53 + 128;
__device__ __align__(1024) unsigned g_cnt[CNT_N * 32];
#define TR(slot) do {} while (0)
#define TRC(cond, slot) do {} while (0)
#define TRD(dep, slot) do {} while (0)
#define RETRY_COUNT()

struct Params {
    const __nv_bfloat16 *ssmk, *shift, *ssmd, *q;
    __nv_bfloat16 *o, *xnp, *fp;
    uint32_t* yp;
    unsigned* cnt;
    long long* trace;
    int kv_swap;
    CUtensorMap mkv, wg, wu, wp, wd, xn, out, f, hg, hu, hp, xr;
};

constexpr int NST = 8, STB = 16384;
constexpr int OFF_R = 0, OFF_A = 32768, OFF_RING = 98304;
constexpr int H_AOWN = 0, H_AREM = 16384, H_BOWN = 32768, H_BREM = 40960, H_HOWN = 49152, H_HREM = 53248;
constexpr int PW_PITCH = 8224, KB_PITCH = 4112, KV_BYTES = 33 * 64;
constexpr int OFF_PW = OFF_RING + 6 * STB, OFF_KB = OFF_RING;
constexpr int OFF_SC = OFF_R, OFF_KV = OFF_A;
constexpr int OFF_BAR = OFF_RING + NST * STB + 128, OFF_TBL = OFF_BAR + 640, OFF_TAG = OFF_TBL + 16, OFF_ZERO = OFF_TBL + 128, OFF_TRACE = OFF_ZERO + 1024, SMEM_BYTES = OFF_TRACE + 1024;
static_assert(OFF_PW + 4 * PW_PITCH <= OFF_BAR, "conv overlay");
static_assert(SMEM_BYTES <= 232448, "smem");
constexpr int B_FULL = 0, B_AFULL = 23, B_ALAND = 31, B_CONV = 39, B_HAREM = 40, B_HBREM = 41, B_HACK = 42, B_Y1 = 44, B_HINT = 45, B_AUX = 47, B_YD = 51, B_W = 53, B_RETRY = 55, B_PACK = 59,
              B_UFULL = 60, B_HBOWN = 62, B_AEMPTY = 63, B_P2DONE = 64, B_HFREE = 65, B_K2 = 66, B_ATMP = 67, B_OWN = 68, B_KVL = 71, B_KV = 72;
constexpr int NB_TURN = 1, NB_WG = 3, NB_LN = 5, NB_YS = 6, NB_FIN = 7;
#define PACE_H 160
#define PACE_A 256
#define XRED 1
#define XSTG 1
#define PACE3 216
#define XPACE 512
#define ZPACE 128
#define PACE_A0 200
#define PUB 0
#define EARLY1 0
#define WFENCE 0
#define HDELAY 400
#define PACE_B 100
#define VT 0
#define LATEPF 1
#define XDEL 0
#define NSLEEP 32
#define NOCHK 0
#define ZON 1
#define ZREL 1
#define HNOW 1
#define PREFILL 0
#define SPEC 2
#define SDELAY 500
#define SDELAY2 500
#define PACE 160

constexpr uint32_t SPIN_LIMIT = 1u << 22;

__device__ __forceinline__ uint32_t smem_u32(const void* p) { return (uint32_t)__cvta_generic_to_shared(p); }
template <class T> __device__ __forceinline__ T here(T v) { asm volatile("" : "+r"(v)); return v; }
__device__ __forceinline__ void mbar_init(uint32_t bar, uint32_t cnt) { asm volatile("mbarrier.init.shared::cta.b64 [%0], %1;" ::"r"(bar), "r"(cnt) : "memory"); }
__device__ __forceinline__ void mbar_expect_tx(uint32_t bar, uint32_t bytes) { asm volatile("mbarrier.arrive.expect_tx.shared::cta.b64 _, [%0], %1;" ::"r"(bar), "r"(bytes) : "memory"); }
__device__ __forceinline__ void mbar_arrive(uint32_t bar) { asm volatile("mbarrier.arrive.shared::cta.b64 _, [%0];" ::"r"(bar) : "memory"); }
__device__ __forceinline__ void mbar_arrive_n(uint32_t bar, uint32_t n) { asm volatile("mbarrier.arrive.shared::cta.b64 _, [%0], %1;" ::"r"(bar), "r"(n) : "memory"); }
__device__ __forceinline__ void mbar_arrive_remote(uint32_t bar) { asm volatile("mbarrier.arrive.shared::cluster.b64 _, [%0];" ::"r"(bar) : "memory"); }
__device__ __forceinline__ void mbar_arrive_remote_n(uint32_t bar, uint32_t n) { asm volatile("mbarrier.arrive.shared::cluster.b64 _, [%0], %1;" ::"r"(bar), "r"(n) : "memory"); }
__device__ __forceinline__ void mbar_wait(uint32_t bar, uint32_t parity) {
    asm volatile("{\n.reg .pred p;\nLW:\nmbarrier.try_wait.parity.shared::cta.b64 p, [%0], %1;\n@!p bra.uni LW;\n}" ::"r"(bar), "r"(parity) : "memory");
}
__device__ __forceinline__ bool mbar_test(uint32_t bar, uint32_t parity) {
    uint32_t ok;
    asm volatile("{\n.reg .pred p;\nmbarrier.test_wait.parity.shared::cta.b64 p, [%1], %2;\nselp.u32 %0, 1, 0, p;\n}" : "=r"(ok) : "r"(bar), "r"(parity) : "memory");
    return ok;
}
__device__ __forceinline__ uint32_t mapa(uint32_t addr, uint32_t rank) { uint32_t r; asm volatile("mapa.shared::cluster.u32 %0, %1, %2;" : "=r"(r) : "r"(addr), "r"(rank)); return r; }
__device__ __forceinline__ bool elect() { uint32_t p; asm volatile("{\n.reg .pred p;\nelect.sync _|p, 0xffffffff;\nselp.u32 %0, 1, 0, p;\n}" : "=r"(p)); return p; }
__device__ __forceinline__ void cluster_arrive() { asm volatile("barrier.cluster.arrive.relaxed.aligned;" ::: "memory"); }
__device__ __forceinline__ void cluster_wait() { asm volatile("barrier.cluster.wait.aligned;" ::: "memory"); }
__device__ __forceinline__ void nb_sync(int id, int n) { asm volatile("bar.sync %0, %1;" ::"r"(id), "r"(n) : "memory"); }
__device__ __forceinline__ void nb_arrive(int id, int n) { asm volatile("bar.arrive %0, %1;" ::"r"(id), "r"(n) : "memory"); }
__device__ __forceinline__ void fence_async_smem() { asm volatile("fence.proxy.async.shared::cta;" ::: "memory"); }
__device__ __forceinline__ void fence_async_global() { asm volatile("fence.proxy.async.global;" ::: "memory"); }
__device__ __forceinline__ void tma2d(uint32_t dst, const CUtensorMap* tm, int c0, int c1, uint32_t bar) {
    asm volatile("cp.async.bulk.tensor.2d.shared::cluster.global.mbarrier::complete_tx::bytes [%0], [%1, {%3, %4}], [%2];"
                 ::"r"(dst), "l"(tm), "r"(bar), "r"(c0), "r"(c1) : "memory");
}
__device__ __forceinline__ void tma2d_w(uint32_t dst, const CUtensorMap* tm, int c0, int c1, uint32_t bar) {
    asm volatile("{\n.reg .pred p;\nelect.sync _|p, 0xffffffff;\n"
                 "@p cp.async.bulk.tensor.2d.shared::cluster.global.mbarrier::complete_tx::bytes [%0], [%1, {%3, %4}], [%2];\n}"
                 ::"r"(dst), "l"(tm), "r"(bar), "r"(c0), "r"(c1) : "memory");
}
__device__ __forceinline__ void tma2d_mc(uint32_t dst, const CUtensorMap* tm, int c0, int c1, uint32_t bar) {
    asm volatile("cp.async.bulk.tensor.2d.shared::cluster.global.mbarrier::complete_tx::bytes.multicast::cluster [%0], [%1, {%3, %4}], [%2], %5;"
                 ::"r"(dst), "l"(tm), "r"(bar), "r"(c0), "r"(c1), "h"((uint16_t)3) : "memory");
}
__device__ __forceinline__ void tma3d(uint32_t dst, const CUtensorMap* tm, int c0, int c1, int c2, uint32_t bar) {
    asm volatile("cp.async.bulk.tensor.3d.shared::cluster.global.mbarrier::complete_tx::bytes [%0], [%1, {%3, %4, %5}], [%2];"
                 ::"r"(dst), "l"(tm), "r"(bar), "r"(c0), "r"(c1), "r"(c2) : "memory");
}
__device__ __forceinline__ void tma4d(uint32_t dst, const CUtensorMap* tm, int c0, int c1, uint32_t bar) {
    asm volatile("cp.async.bulk.tensor.4d.shared::cluster.global.mbarrier::complete_tx::bytes [%0], [%1, {%3, %4, 0, 0}], [%2];"
                 ::"r"(dst), "l"(tm), "r"(bar), "r"(c0), "r"(c1) : "memory");
}
__device__ __forceinline__ void tma_prefetch2d(const CUtensorMap* tm, int c0, int c1) {
    asm volatile("cp.async.bulk.prefetch.tensor.2d.L2.global [%0, {%1, %2}];" ::"l"(tm), "r"(c0), "r"(c1) : "memory");
}
__device__ __forceinline__ void tma_store2d(const CUtensorMap* tm, int c0, int c1, uint32_t src) {
    asm volatile("cp.async.bulk.tensor.2d.global.shared::cta.bulk_group [%0, {%1, %2}], [%3];" ::"l"(tm), "r"(c0), "r"(c1), "r"(src) : "memory");
}
__device__ __forceinline__ void tma_store3d_w(const CUtensorMap* tm, int c1, int c2, uint32_t src) {
    asm volatile("{\n.reg .pred p;\nelect.sync _|p, 0xffffffff;\n"
                 "@p cp.async.bulk.tensor.3d.global.shared::cta.bulk_group [%0, {0, %1, %2}], [%3];\n}" ::"l"(tm), "r"(c1), "r"(c2), "r"(src) : "memory");
}
__device__ __forceinline__ void tma_red3d_w(const CUtensorMap* tm, int c1, int c2, uint32_t src) {
    asm volatile("{\n.reg .pred p;\nelect.sync _|p, 0xffffffff;\n"
                 "@p cp.reduce.async.bulk.tensor.3d.global.shared::cta.add.bulk_group [%0, {0, %1, %2}], [%3];\n}" ::"l"(tm), "r"(c1), "r"(c2), "r"(src) : "memory");
}
__device__ __forceinline__ void bulk_g2s(uint32_t dst, const void* src, uint32_t bytes, uint32_t bar) {
    asm volatile("cp.async.bulk.shared::cluster.global.mbarrier::complete_tx::bytes [%0], [%1], %2, [%3];" ::"r"(dst), "l"(src), "r"(bytes), "r"(bar) : "memory");
}
__device__ __forceinline__ void bulk_s2s(uint32_t dst, uint32_t src, uint32_t bytes, uint32_t bar) {
    asm volatile("cp.async.bulk.shared::cluster.shared::cta.mbarrier::complete_tx::bytes [%0], [%1], %2, [%3];" ::"r"(dst), "r"(src), "r"(bytes), "r"(bar) : "memory");
}
__device__ __forceinline__ void bulk_s2g(void* dst, uint32_t src, uint32_t bytes) {
    asm volatile("cp.async.bulk.global.shared::cta.bulk_group [%0], [%1], %2;" ::"l"(dst), "r"(src), "r"(bytes) : "memory");
}
__device__ __forceinline__ void bulk_prefetch(const void* src, uint32_t bytes) { asm volatile("cp.async.bulk.prefetch.L2.global [%0], %1;" ::"l"(src), "r"(bytes) : "memory"); }
__device__ __forceinline__ void bulk_commit() { asm volatile("cp.async.bulk.commit_group;" ::: "memory"); }
__device__ __forceinline__ void bulk_wait_read() { asm volatile("cp.async.bulk.wait_group.read 0;" ::: "memory"); }
__device__ __forceinline__ void bulk_wait() { asm volatile("cp.async.bulk.wait_group 0;" ::: "memory"); }
__device__ __forceinline__ void prefetch_tmap(const CUtensorMap* tm) { asm volatile("prefetch.tensormap [%0];" ::"l"(tm) : "memory"); }
#define SPINMODE 2
__device__ __forceinline__ void wait_until(uint32_t t) {
    asm volatile("{\n.reg .pred p;\n.reg .u32 c, h;\n.reg .u64 w;\nLP:\nmov.u64 w, %%clock64;\nmov.b64 {c, h}, w;\nsub.s32 c, c, %0;\nsetp.lt.s32 p, c, 0;\n@p bra.uni LP;\n}" ::"r"(t) : "memory");
}
__device__ __forceinline__ void pace(uint32_t t0, uint32_t dt) { wait_until(t0 + dt); }
__device__ __forceinline__ void hint(unsigned* p) { asm volatile("red.relaxed.gpu.global.add.u32 [%0], 1;" ::"l"(p) : "memory"); }
__device__ __forceinline__ void release(unsigned* p) { asm volatile("red.release.gpu.global.add.u32 [%0], 1;" ::"l"(p) : "memory"); }
__device__ __forceinline__ void poll(const unsigned* p, unsigned target) {
    unsigned v;
    asm volatile("ld.relaxed.gpu.global.u32 %0, [%1];" : "=r"(v) : "l"(p) : "memory");
    pace(clock(), 200);
    asm volatile("{\n.reg .pred p;\n.reg .u32 w;\n"
                 "LP:\nld.relaxed.gpu.global.u32 w, [%1];\nsub.s32 %0, %0, %2;\nsetp.ge.s32 p, %0, 0;\n@p bra.uni LD;\n"
                 "ld.relaxed.gpu.global.u32 %0, [%1];\nsub.s32 w, w, %2;\nsetp.lt.s32 p, w, 0;\n@p bra.uni LP;\nLD:\n}"
                 : "+r"(v) : "l"(p), "r"(target) : "memory");
}
__device__ __forceinline__ void wg_fence() { asm volatile("wgmma.fence.sync.aligned;" ::: "memory"); }
__device__ __forceinline__ void wg_commit() { asm volatile("wgmma.commit_group.sync.aligned;" ::: "memory"); }
template <int N> __device__ __forceinline__ void wg_wait() { asm volatile("wgmma.wait_group.sync.aligned %0;" ::"n"(N) : "memory"); }
template <int N> __device__ __forceinline__ void pin(float (&d)[N]) {
#pragma unroll
    for (int i = 0; i < N; i++) asm volatile("" : "+f"(d[i])::"memory");
}
constexpr uint32_t SMEM0 = 1024;
__host__ __device__ constexpr uint32_t desc_lo(uint32_t off, uint32_t lbo) { return ((SMEM0 + off) >> 4) | ((lbo >> 4) << 16); }
constexpr uint32_t desc_hi(uint32_t sbo, uint32_t swz) { return (sbo >> 4) | (swz << 30); }
constexpr uint32_t HI128 = desc_hi(1024, 1), HI64 = desc_hi(512, 2), HI0 = desc_hi(128, 0);
__device__ __forceinline__ uint32_t lds32(uint32_t a) { uint32_t v; asm volatile("ld.shared.u32 %0, [%1];" : "=r"(v) : "r"(a) : "memory"); return v; }
__device__ __forceinline__ uint4 lds128(uint32_t a) { uint4 v; asm volatile("ld.shared.v4.u32 {%0,%1,%2,%3}, [%4];" : "=r"(v.x), "=r"(v.y), "=r"(v.z), "=r"(v.w) : "r"(a) : "memory"); return v; }
__device__ __forceinline__ uint2 lds64(uint32_t a) { uint2 v; asm volatile("ld.shared.v2.u32 {%0,%1}, [%2];" : "=r"(v.x), "=r"(v.y) : "r"(a) : "memory"); return v; }
__device__ __forceinline__ void sts32(uint32_t a, uint32_t v) { asm volatile("st.shared.u32 [%0], %1;" ::"r"(a), "r"(v) : "memory"); }
__device__ __forceinline__ void sts128(uint32_t a, uint32_t x, uint32_t y, uint32_t z, uint32_t w) { asm volatile("st.shared.v4.u32 [%0], {%1,%2,%3,%4};" ::"r"(a), "r"(x), "r"(y), "r"(z), "r"(w) : "memory"); }
__device__ __forceinline__ void stsm4(uint32_t a, uint32_t x, uint32_t y, uint32_t z, uint32_t w) {
    asm volatile("stmatrix.sync.aligned.m8n8.x4.shared.b16 [%0], {%1,%2,%3,%4};" ::"r"(a), "r"(x), "r"(y), "r"(z), "r"(w) : "memory");
}
__device__ __forceinline__ uint32_t pack2(float lo, float hi) { uint32_t r; asm("cvt.rn.bf16x2.f32 %0, %1, %2;" : "=r"(r) : "f"(hi), "f"(lo)); return r; }
__device__ __forceinline__ float blo(uint32_t w) { return __uint_as_float(w << 16); }
__device__ __forceinline__ float bhi(uint32_t w) { return __uint_as_float(w & 0xffff0000u); }
__device__ __forceinline__ float rbf(float x) { return bhi(pack2(0.f, x)); }
__device__ __forceinline__ uint32_t bmul(uint32_t a, uint32_t b) { uint32_t r; asm("mul.rn.bf16x2 %0, %1, %2;" : "=r"(r) : "r"(a), "r"(b)); return r; }
__device__ __forceinline__ uint32_t badd(uint32_t a, uint32_t b) { uint32_t r; asm("add.rn.bf16x2 %0, %1, %2;" : "=r"(r) : "r"(a), "r"(b)); return r; }
__device__ __forceinline__ uint4 ldg_nc128(const void* p) { uint4 v; asm volatile("ld.global.nc.L1::no_allocate.L2::128B.v4.u32 {%0,%1,%2,%3}, [%4];" : "=r"(v.x), "=r"(v.y), "=r"(v.z), "=r"(v.w) : "l"(p)); return v; }
__device__ __forceinline__ uint32_t bfma(uint32_t a, uint32_t b, uint32_t c) { uint32_t r; asm("fma.rn.bf16x2 %0, %1, %2, %3;" : "=r"(r) : "r"(a), "r"(b), "r"(c)); return r; }
__device__ __forceinline__ uint32_t differ(uint32_t a, uint32_t b, uint32_t t) { uint32_t r; asm volatile("lop3.b32 %0, %1, %2, %3, 0x7e;" : "=r"(r) : "r"(a), "r"(b), "r"(t)); return r; }
__device__ __forceinline__ void prefetch_l2(const void* p) { asm volatile("prefetch.global.L2 [%0];" ::"l"(p)); }
__device__ __forceinline__ float glu(float hg, float hu) {
    float t;
    asm("tanh.approx.f32 %0, %1;" : "=f"(t) : "f"(hg));
    return fmaf(t, hu, hu);
}

template <int OFF> __device__ __forceinline__ void wg_ss256(float (&d)[128], uint32_t alo, uint32_t ahi, uint32_t blo, uint32_t bhi, int sd) {
  asm volatile("{\n.reg .pred p;\n.reg .b64 da, db;\nsetp.ne.b32 p, %132, 0;\nmov.b64 da, {%128, %129};\nmov.b64 db, {%130, %131};\n"
    "wgmma.mma_async.sync.aligned.m64n256k16.f32.bf16.bf16 {%0,%1,%2,%3,%4,%5,%6,%7,%8,%9,%10,%11,%12,%13,%14,%15,%16,%17,%18,%19,%20,%21,%22,%23,%24,%25,%26,%27,%28,%29,%30,%31,%32,%33,%34,%35,%36,%37,%38,%39,%40,%41,%42,%43,%44,%45,%46,%47,%48,%49,%50,%51,%52,%53,%54,%55,%56,%57,%58,%59,%60,%61,%62,%63,%64,%65,%66,%67,%68,%69,%70,%71,%72,%73,%74,%75,%76,%77,%78,%79,%80,%81,%82,%83,%84,%85,%86,%87,%88,%89,%90,%91,%92,%93,%94,%95,%96,%97,%98,%99,%100,%101,%102,%103,%104,%105,%106,%107,%108,%109,%110,%111,%112,%113,%114,%115,%116,%117,%118,%119,%120,%121,%122,%123,%124,%125,%126,%127}, da, db, p, 1, 1, 0, 1;\n}\n"
    : "+f"(d[OFF+0]),"+f"(d[OFF+1]),"+f"(d[OFF+2]),"+f"(d[OFF+3]),"+f"(d[OFF+4]),"+f"(d[OFF+5]),"+f"(d[OFF+6]),"+f"(d[OFF+7]),"+f"(d[OFF+8]),"+f"(d[OFF+9]),"+f"(d[OFF+10]),"+f"(d[OFF+11]),"+f"(d[OFF+12]),"+f"(d[OFF+13]),"+f"(d[OFF+14]),"+f"(d[OFF+15]),"+f"(d[OFF+16]),"+f"(d[OFF+17]),"+f"(d[OFF+18]),"+f"(d[OFF+19]),"+f"(d[OFF+20]),"+f"(d[OFF+21]),"+f"(d[OFF+22]),"+f"(d[OFF+23]),"+f"(d[OFF+24]),"+f"(d[OFF+25]),"+f"(d[OFF+26]),"+f"(d[OFF+27]),"+f"(d[OFF+28]),"+f"(d[OFF+29]),"+f"(d[OFF+30]),"+f"(d[OFF+31]),"+f"(d[OFF+32]),"+f"(d[OFF+33]),"+f"(d[OFF+34]),"+f"(d[OFF+35]),"+f"(d[OFF+36]),"+f"(d[OFF+37]),"+f"(d[OFF+38]),"+f"(d[OFF+39]),"+f"(d[OFF+40]),"+f"(d[OFF+41]),"+f"(d[OFF+42]),"+f"(d[OFF+43]),"+f"(d[OFF+44]),"+f"(d[OFF+45]),"+f"(d[OFF+46]),"+f"(d[OFF+47]),"+f"(d[OFF+48]),"+f"(d[OFF+49]),"+f"(d[OFF+50]),"+f"(d[OFF+51]),"+f"(d[OFF+52]),"+f"(d[OFF+53]),"+f"(d[OFF+54]),"+f"(d[OFF+55]),"+f"(d[OFF+56]),"+f"(d[OFF+57]),"+f"(d[OFF+58]),"+f"(d[OFF+59]),"+f"(d[OFF+60]),"+f"(d[OFF+61]),"+f"(d[OFF+62]),"+f"(d[OFF+63]),"+f"(d[OFF+64]),"+f"(d[OFF+65]),"+f"(d[OFF+66]),"+f"(d[OFF+67]),"+f"(d[OFF+68]),"+f"(d[OFF+69]),"+f"(d[OFF+70]),"+f"(d[OFF+71]),"+f"(d[OFF+72]),"+f"(d[OFF+73]),"+f"(d[OFF+74]),"+f"(d[OFF+75]),"+f"(d[OFF+76]),"+f"(d[OFF+77]),"+f"(d[OFF+78]),"+f"(d[OFF+79]),"+f"(d[OFF+80]),"+f"(d[OFF+81]),"+f"(d[OFF+82]),"+f"(d[OFF+83]),"+f"(d[OFF+84]),"+f"(d[OFF+85]),"+f"(d[OFF+86]),"+f"(d[OFF+87]),"+f"(d[OFF+88]),"+f"(d[OFF+89]),"+f"(d[OFF+90]),"+f"(d[OFF+91]),"+f"(d[OFF+92]),"+f"(d[OFF+93]),"+f"(d[OFF+94]),"+f"(d[OFF+95]),"+f"(d[OFF+96]),"+f"(d[OFF+97]),"+f"(d[OFF+98]),"+f"(d[OFF+99]),"+f"(d[OFF+100]),"+f"(d[OFF+101]),"+f"(d[OFF+102]),"+f"(d[OFF+103]),"+f"(d[OFF+104]),"+f"(d[OFF+105]),"+f"(d[OFF+106]),"+f"(d[OFF+107]),"+f"(d[OFF+108]),"+f"(d[OFF+109]),"+f"(d[OFF+110]),"+f"(d[OFF+111]),"+f"(d[OFF+112]),"+f"(d[OFF+113]),"+f"(d[OFF+114]),"+f"(d[OFF+115]),"+f"(d[OFF+116]),"+f"(d[OFF+117]),"+f"(d[OFF+118]),"+f"(d[OFF+119]),"+f"(d[OFF+120]),"+f"(d[OFF+121]),"+f"(d[OFF+122]),"+f"(d[OFF+123]),"+f"(d[OFF+124]),"+f"(d[OFF+125]),"+f"(d[OFF+126]),"+f"(d[OFF+127])
    : "r"(alo), "r"(ahi), "r"(blo), "r"(bhi), "r"(sd));
}
template <int OFF> __device__ __forceinline__ void wg_ss192(float (&d)[96], uint32_t alo, uint32_t ahi, uint32_t blo, uint32_t bhi, int sd) {
  asm volatile("{\n.reg .pred p;\n.reg .b64 da, db;\nsetp.ne.b32 p, %100, 0;\nmov.b64 da, {%96, %97};\nmov.b64 db, {%98, %99};\n"
    "wgmma.mma_async.sync.aligned.m64n192k16.f32.bf16.bf16 {%0,%1,%2,%3,%4,%5,%6,%7,%8,%9,%10,%11,%12,%13,%14,%15,%16,%17,%18,%19,%20,%21,%22,%23,%24,%25,%26,%27,%28,%29,%30,%31,%32,%33,%34,%35,%36,%37,%38,%39,%40,%41,%42,%43,%44,%45,%46,%47,%48,%49,%50,%51,%52,%53,%54,%55,%56,%57,%58,%59,%60,%61,%62,%63,%64,%65,%66,%67,%68,%69,%70,%71,%72,%73,%74,%75,%76,%77,%78,%79,%80,%81,%82,%83,%84,%85,%86,%87,%88,%89,%90,%91,%92,%93,%94,%95}, da, db, p, 1, 1, 0, 1;\n}\n"
    : "+f"(d[OFF+0]),"+f"(d[OFF+1]),"+f"(d[OFF+2]),"+f"(d[OFF+3]),"+f"(d[OFF+4]),"+f"(d[OFF+5]),"+f"(d[OFF+6]),"+f"(d[OFF+7]),"+f"(d[OFF+8]),"+f"(d[OFF+9]),"+f"(d[OFF+10]),"+f"(d[OFF+11]),"+f"(d[OFF+12]),"+f"(d[OFF+13]),"+f"(d[OFF+14]),"+f"(d[OFF+15]),"+f"(d[OFF+16]),"+f"(d[OFF+17]),"+f"(d[OFF+18]),"+f"(d[OFF+19]),"+f"(d[OFF+20]),"+f"(d[OFF+21]),"+f"(d[OFF+22]),"+f"(d[OFF+23]),"+f"(d[OFF+24]),"+f"(d[OFF+25]),"+f"(d[OFF+26]),"+f"(d[OFF+27]),"+f"(d[OFF+28]),"+f"(d[OFF+29]),"+f"(d[OFF+30]),"+f"(d[OFF+31]),"+f"(d[OFF+32]),"+f"(d[OFF+33]),"+f"(d[OFF+34]),"+f"(d[OFF+35]),"+f"(d[OFF+36]),"+f"(d[OFF+37]),"+f"(d[OFF+38]),"+f"(d[OFF+39]),"+f"(d[OFF+40]),"+f"(d[OFF+41]),"+f"(d[OFF+42]),"+f"(d[OFF+43]),"+f"(d[OFF+44]),"+f"(d[OFF+45]),"+f"(d[OFF+46]),"+f"(d[OFF+47]),"+f"(d[OFF+48]),"+f"(d[OFF+49]),"+f"(d[OFF+50]),"+f"(d[OFF+51]),"+f"(d[OFF+52]),"+f"(d[OFF+53]),"+f"(d[OFF+54]),"+f"(d[OFF+55]),"+f"(d[OFF+56]),"+f"(d[OFF+57]),"+f"(d[OFF+58]),"+f"(d[OFF+59]),"+f"(d[OFF+60]),"+f"(d[OFF+61]),"+f"(d[OFF+62]),"+f"(d[OFF+63]),"+f"(d[OFF+64]),"+f"(d[OFF+65]),"+f"(d[OFF+66]),"+f"(d[OFF+67]),"+f"(d[OFF+68]),"+f"(d[OFF+69]),"+f"(d[OFF+70]),"+f"(d[OFF+71]),"+f"(d[OFF+72]),"+f"(d[OFF+73]),"+f"(d[OFF+74]),"+f"(d[OFF+75]),"+f"(d[OFF+76]),"+f"(d[OFF+77]),"+f"(d[OFF+78]),"+f"(d[OFF+79]),"+f"(d[OFF+80]),"+f"(d[OFF+81]),"+f"(d[OFF+82]),"+f"(d[OFF+83]),"+f"(d[OFF+84]),"+f"(d[OFF+85]),"+f"(d[OFF+86]),"+f"(d[OFF+87]),"+f"(d[OFF+88]),"+f"(d[OFF+89]),"+f"(d[OFF+90]),"+f"(d[OFF+91]),"+f"(d[OFF+92]),"+f"(d[OFF+93]),"+f"(d[OFF+94]),"+f"(d[OFF+95])
    : "r"(alo), "r"(ahi), "r"(blo), "r"(bhi), "r"(sd));
}
template <int OFF> __device__ __forceinline__ void wg_ss128(float (&d)[64], uint32_t alo, uint32_t ahi, uint32_t blo, uint32_t bhi, int sd) {
  asm volatile("{\n.reg .pred p;\n.reg .b64 da, db;\nsetp.ne.b32 p, %68, 0;\nmov.b64 da, {%64, %65};\nmov.b64 db, {%66, %67};\n"
    "wgmma.mma_async.sync.aligned.m64n128k16.f32.bf16.bf16 {%0,%1,%2,%3,%4,%5,%6,%7,%8,%9,%10,%11,%12,%13,%14,%15,%16,%17,%18,%19,%20,%21,%22,%23,%24,%25,%26,%27,%28,%29,%30,%31,%32,%33,%34,%35,%36,%37,%38,%39,%40,%41,%42,%43,%44,%45,%46,%47,%48,%49,%50,%51,%52,%53,%54,%55,%56,%57,%58,%59,%60,%61,%62,%63}, da, db, p, 1, 1, 0, 1;\n}\n"
    : "+f"(d[OFF+0]),"+f"(d[OFF+1]),"+f"(d[OFF+2]),"+f"(d[OFF+3]),"+f"(d[OFF+4]),"+f"(d[OFF+5]),"+f"(d[OFF+6]),"+f"(d[OFF+7]),"+f"(d[OFF+8]),"+f"(d[OFF+9]),"+f"(d[OFF+10]),"+f"(d[OFF+11]),"+f"(d[OFF+12]),"+f"(d[OFF+13]),"+f"(d[OFF+14]),"+f"(d[OFF+15]),"+f"(d[OFF+16]),"+f"(d[OFF+17]),"+f"(d[OFF+18]),"+f"(d[OFF+19]),"+f"(d[OFF+20]),"+f"(d[OFF+21]),"+f"(d[OFF+22]),"+f"(d[OFF+23]),"+f"(d[OFF+24]),"+f"(d[OFF+25]),"+f"(d[OFF+26]),"+f"(d[OFF+27]),"+f"(d[OFF+28]),"+f"(d[OFF+29]),"+f"(d[OFF+30]),"+f"(d[OFF+31]),"+f"(d[OFF+32]),"+f"(d[OFF+33]),"+f"(d[OFF+34]),"+f"(d[OFF+35]),"+f"(d[OFF+36]),"+f"(d[OFF+37]),"+f"(d[OFF+38]),"+f"(d[OFF+39]),"+f"(d[OFF+40]),"+f"(d[OFF+41]),"+f"(d[OFF+42]),"+f"(d[OFF+43]),"+f"(d[OFF+44]),"+f"(d[OFF+45]),"+f"(d[OFF+46]),"+f"(d[OFF+47]),"+f"(d[OFF+48]),"+f"(d[OFF+49]),"+f"(d[OFF+50]),"+f"(d[OFF+51]),"+f"(d[OFF+52]),"+f"(d[OFF+53]),"+f"(d[OFF+54]),"+f"(d[OFF+55]),"+f"(d[OFF+56]),"+f"(d[OFF+57]),"+f"(d[OFF+58]),"+f"(d[OFF+59]),"+f"(d[OFF+60]),"+f"(d[OFF+61]),"+f"(d[OFF+62]),"+f"(d[OFF+63])
    : "r"(alo), "r"(ahi), "r"(blo), "r"(bhi), "r"(sd));
}
__device__ __forceinline__ void wg_rs128(float (&d)[64], const uint32_t (&a)[4], uint32_t blo, uint32_t bhi, int sd) {
  asm volatile("{\n.reg .pred p;\n.reg .b64 db;\nsetp.ne.b32 p, %70, 0;\nmov.b64 db, {%68, %69};\n"
    "wgmma.mma_async.sync.aligned.m64n128k16.f32.bf16.bf16 {%0,%1,%2,%3,%4,%5,%6,%7,%8,%9,%10,%11,%12,%13,%14,%15,%16,%17,%18,%19,%20,%21,%22,%23,%24,%25,%26,%27,%28,%29,%30,%31,%32,%33,%34,%35,%36,%37,%38,%39,%40,%41,%42,%43,%44,%45,%46,%47,%48,%49,%50,%51,%52,%53,%54,%55,%56,%57,%58,%59,%60,%61,%62,%63}, {%64,%65,%66,%67}, db, p, 1, 1, 0;\n}\n"
    : "+f"(d[0]),"+f"(d[1]),"+f"(d[2]),"+f"(d[3]),"+f"(d[4]),"+f"(d[5]),"+f"(d[6]),"+f"(d[7]),"+f"(d[8]),"+f"(d[9]),"+f"(d[10]),"+f"(d[11]),"+f"(d[12]),"+f"(d[13]),"+f"(d[14]),"+f"(d[15]),"+f"(d[16]),"+f"(d[17]),"+f"(d[18]),"+f"(d[19]),"+f"(d[20]),"+f"(d[21]),"+f"(d[22]),"+f"(d[23]),"+f"(d[24]),"+f"(d[25]),"+f"(d[26]),"+f"(d[27]),"+f"(d[28]),"+f"(d[29]),"+f"(d[30]),"+f"(d[31]),"+f"(d[32]),"+f"(d[33]),"+f"(d[34]),"+f"(d[35]),"+f"(d[36]),"+f"(d[37]),"+f"(d[38]),"+f"(d[39]),"+f"(d[40]),"+f"(d[41]),"+f"(d[42]),"+f"(d[43]),"+f"(d[44]),"+f"(d[45]),"+f"(d[46]),"+f"(d[47]),"+f"(d[48]),"+f"(d[49]),"+f"(d[50]),"+f"(d[51]),"+f"(d[52]),"+f"(d[53]),"+f"(d[54]),"+f"(d[55]),"+f"(d[56]),"+f"(d[57]),"+f"(d[58]),"+f"(d[59]),"+f"(d[60]),"+f"(d[61]),"+f"(d[62]),"+f"(d[63])
    : "r"(a[0]), "r"(a[1]), "r"(a[2]), "r"(a[3]), "r"(blo), "r"(bhi), "r"(sd));
}
__device__ __forceinline__ void wg_rs112(float (&d)[64], const uint32_t (&a)[4], uint32_t blo, uint32_t bhi, int sd) {
  asm volatile("{\n.reg .pred p;\n.reg .b64 db;\nsetp.ne.b32 p, %62, 0;\nmov.b64 db, {%60, %61};\n"
    "wgmma.mma_async.sync.aligned.m64n112k16.f32.bf16.bf16 {%0,%1,%2,%3,%4,%5,%6,%7,%8,%9,%10,%11,%12,%13,%14,%15,%16,%17,%18,%19,%20,%21,%22,%23,%24,%25,%26,%27,%28,%29,%30,%31,%32,%33,%34,%35,%36,%37,%38,%39,%40,%41,%42,%43,%44,%45,%46,%47,%48,%49,%50,%51,%52,%53,%54,%55}, {%56,%57,%58,%59}, db, p, 1, 1, 0;\n}\n"
    : "+f"(d[0]),"+f"(d[1]),"+f"(d[2]),"+f"(d[3]),"+f"(d[4]),"+f"(d[5]),"+f"(d[6]),"+f"(d[7]),"+f"(d[8]),"+f"(d[9]),"+f"(d[10]),"+f"(d[11]),"+f"(d[12]),"+f"(d[13]),"+f"(d[14]),"+f"(d[15]),"+f"(d[16]),"+f"(d[17]),"+f"(d[18]),"+f"(d[19]),"+f"(d[20]),"+f"(d[21]),"+f"(d[22]),"+f"(d[23]),"+f"(d[24]),"+f"(d[25]),"+f"(d[26]),"+f"(d[27]),"+f"(d[28]),"+f"(d[29]),"+f"(d[30]),"+f"(d[31]),"+f"(d[32]),"+f"(d[33]),"+f"(d[34]),"+f"(d[35]),"+f"(d[36]),"+f"(d[37]),"+f"(d[38]),"+f"(d[39]),"+f"(d[40]),"+f"(d[41]),"+f"(d[42]),"+f"(d[43]),"+f"(d[44]),"+f"(d[45]),"+f"(d[46]),"+f"(d[47]),"+f"(d[48]),"+f"(d[49]),"+f"(d[50]),"+f"(d[51]),"+f"(d[52]),"+f"(d[53]),"+f"(d[54]),"+f"(d[55])
    : "r"(a[0]), "r"(a[1]), "r"(a[2]), "r"(a[3]), "r"(blo), "r"(bhi), "r"(sd));
}
__device__ __forceinline__ void wg_rs96(float (&d)[64], const uint32_t (&a)[4], uint32_t blo, uint32_t bhi, int sd) {
  asm volatile("{\n.reg .pred p;\n.reg .b64 db;\nsetp.ne.b32 p, %54, 0;\nmov.b64 db, {%52, %53};\n"
    "wgmma.mma_async.sync.aligned.m64n96k16.f32.bf16.bf16 {%0,%1,%2,%3,%4,%5,%6,%7,%8,%9,%10,%11,%12,%13,%14,%15,%16,%17,%18,%19,%20,%21,%22,%23,%24,%25,%26,%27,%28,%29,%30,%31,%32,%33,%34,%35,%36,%37,%38,%39,%40,%41,%42,%43,%44,%45,%46,%47}, {%48,%49,%50,%51}, db, p, 1, 1, 0;\n}\n"
    : "+f"(d[0]),"+f"(d[1]),"+f"(d[2]),"+f"(d[3]),"+f"(d[4]),"+f"(d[5]),"+f"(d[6]),"+f"(d[7]),"+f"(d[8]),"+f"(d[9]),"+f"(d[10]),"+f"(d[11]),"+f"(d[12]),"+f"(d[13]),"+f"(d[14]),"+f"(d[15]),"+f"(d[16]),"+f"(d[17]),"+f"(d[18]),"+f"(d[19]),"+f"(d[20]),"+f"(d[21]),"+f"(d[22]),"+f"(d[23]),"+f"(d[24]),"+f"(d[25]),"+f"(d[26]),"+f"(d[27]),"+f"(d[28]),"+f"(d[29]),"+f"(d[30]),"+f"(d[31]),"+f"(d[32]),"+f"(d[33]),"+f"(d[34]),"+f"(d[35]),"+f"(d[36]),"+f"(d[37]),"+f"(d[38]),"+f"(d[39]),"+f"(d[40]),"+f"(d[41]),"+f"(d[42]),"+f"(d[43]),"+f"(d[44]),"+f"(d[45]),"+f"(d[46]),"+f"(d[47])
    : "r"(a[0]), "r"(a[1]), "r"(a[2]), "r"(a[3]), "r"(blo), "r"(bhi), "r"(sd));
}
__device__ __forceinline__ void wg_rs80(float (&d)[64], const uint32_t (&a)[4], uint32_t blo, uint32_t bhi, int sd) {
  asm volatile("{\n.reg .pred p;\n.reg .b64 db;\nsetp.ne.b32 p, %46, 0;\nmov.b64 db, {%44, %45};\n"
    "wgmma.mma_async.sync.aligned.m64n80k16.f32.bf16.bf16 {%0,%1,%2,%3,%4,%5,%6,%7,%8,%9,%10,%11,%12,%13,%14,%15,%16,%17,%18,%19,%20,%21,%22,%23,%24,%25,%26,%27,%28,%29,%30,%31,%32,%33,%34,%35,%36,%37,%38,%39}, {%40,%41,%42,%43}, db, p, 1, 1, 0;\n}\n"
    : "+f"(d[0]),"+f"(d[1]),"+f"(d[2]),"+f"(d[3]),"+f"(d[4]),"+f"(d[5]),"+f"(d[6]),"+f"(d[7]),"+f"(d[8]),"+f"(d[9]),"+f"(d[10]),"+f"(d[11]),"+f"(d[12]),"+f"(d[13]),"+f"(d[14]),"+f"(d[15]),"+f"(d[16]),"+f"(d[17]),"+f"(d[18]),"+f"(d[19]),"+f"(d[20]),"+f"(d[21]),"+f"(d[22]),"+f"(d[23]),"+f"(d[24]),"+f"(d[25]),"+f"(d[26]),"+f"(d[27]),"+f"(d[28]),"+f"(d[29]),"+f"(d[30]),"+f"(d[31]),"+f"(d[32]),"+f"(d[33]),"+f"(d[34]),"+f"(d[35]),"+f"(d[36]),"+f"(d[37]),"+f"(d[38]),"+f"(d[39])
    : "r"(a[0]), "r"(a[1]), "r"(a[2]), "r"(a[3]), "r"(blo), "r"(bhi), "r"(sd));
}
__device__ __forceinline__ void wg_rs64(float (&d)[64], const uint32_t (&a)[4], uint32_t blo, uint32_t bhi, int sd) {
  asm volatile("{\n.reg .pred p;\n.reg .b64 db;\nsetp.ne.b32 p, %38, 0;\nmov.b64 db, {%36, %37};\n"
    "wgmma.mma_async.sync.aligned.m64n64k16.f32.bf16.bf16 {%0,%1,%2,%3,%4,%5,%6,%7,%8,%9,%10,%11,%12,%13,%14,%15,%16,%17,%18,%19,%20,%21,%22,%23,%24,%25,%26,%27,%28,%29,%30,%31}, {%32,%33,%34,%35}, db, p, 1, 1, 0;\n}\n"
    : "+f"(d[0]),"+f"(d[1]),"+f"(d[2]),"+f"(d[3]),"+f"(d[4]),"+f"(d[5]),"+f"(d[6]),"+f"(d[7]),"+f"(d[8]),"+f"(d[9]),"+f"(d[10]),"+f"(d[11]),"+f"(d[12]),"+f"(d[13]),"+f"(d[14]),"+f"(d[15]),"+f"(d[16]),"+f"(d[17]),"+f"(d[18]),"+f"(d[19]),"+f"(d[20]),"+f"(d[21]),"+f"(d[22]),"+f"(d[23]),"+f"(d[24]),"+f"(d[25]),"+f"(d[26]),"+f"(d[27]),"+f"(d[28]),"+f"(d[29]),"+f"(d[30]),"+f"(d[31])
    : "r"(a[0]), "r"(a[1]), "r"(a[2]), "r"(a[3]), "r"(blo), "r"(bhi), "r"(sd));
}
__device__ __forceinline__ void wg_rs48(float (&d)[64], const uint32_t (&a)[4], uint32_t blo, uint32_t bhi, int sd) {
  asm volatile("{\n.reg .pred p;\n.reg .b64 db;\nsetp.ne.b32 p, %30, 0;\nmov.b64 db, {%28, %29};\n"
    "wgmma.mma_async.sync.aligned.m64n48k16.f32.bf16.bf16 {%0,%1,%2,%3,%4,%5,%6,%7,%8,%9,%10,%11,%12,%13,%14,%15,%16,%17,%18,%19,%20,%21,%22,%23}, {%24,%25,%26,%27}, db, p, 1, 1, 0;\n}\n"
    : "+f"(d[0]),"+f"(d[1]),"+f"(d[2]),"+f"(d[3]),"+f"(d[4]),"+f"(d[5]),"+f"(d[6]),"+f"(d[7]),"+f"(d[8]),"+f"(d[9]),"+f"(d[10]),"+f"(d[11]),"+f"(d[12]),"+f"(d[13]),"+f"(d[14]),"+f"(d[15]),"+f"(d[16]),"+f"(d[17]),"+f"(d[18]),"+f"(d[19]),"+f"(d[20]),"+f"(d[21]),"+f"(d[22]),"+f"(d[23])
    : "r"(a[0]), "r"(a[1]), "r"(a[2]), "r"(a[3]), "r"(blo), "r"(bhi), "r"(sd));
}
__device__ __forceinline__ void wg_rs32(float (&d)[64], const uint32_t (&a)[4], uint32_t blo, uint32_t bhi, int sd) {
  asm volatile("{\n.reg .pred p;\n.reg .b64 db;\nsetp.ne.b32 p, %22, 0;\nmov.b64 db, {%20, %21};\n"
    "wgmma.mma_async.sync.aligned.m64n32k16.f32.bf16.bf16 {%0,%1,%2,%3,%4,%5,%6,%7,%8,%9,%10,%11,%12,%13,%14,%15}, {%16,%17,%18,%19}, db, p, 1, 1, 0;\n}\n"
    : "+f"(d[0]),"+f"(d[1]),"+f"(d[2]),"+f"(d[3]),"+f"(d[4]),"+f"(d[5]),"+f"(d[6]),"+f"(d[7]),"+f"(d[8]),"+f"(d[9]),"+f"(d[10]),"+f"(d[11]),"+f"(d[12]),"+f"(d[13]),"+f"(d[14]),"+f"(d[15])
    : "r"(a[0]), "r"(a[1]), "r"(a[2]), "r"(a[3]), "r"(blo), "r"(bhi), "r"(sd));
}
__device__ __forceinline__ void wg_rs16(float (&d)[64], const uint32_t (&a)[4], uint32_t blo, uint32_t bhi, int sd) {
  asm volatile("{\n.reg .pred p;\n.reg .b64 db;\nsetp.ne.b32 p, %14, 0;\nmov.b64 db, {%12, %13};\n"
    "wgmma.mma_async.sync.aligned.m64n16k16.f32.bf16.bf16 {%0,%1,%2,%3,%4,%5,%6,%7}, {%8,%9,%10,%11}, db, p, 1, 1, 0;\n}\n"
    : "+f"(d[0]),"+f"(d[1]),"+f"(d[2]),"+f"(d[3]),"+f"(d[4]),"+f"(d[5]),"+f"(d[6]),"+f"(d[7])
    : "r"(a[0]), "r"(a[1]), "r"(a[2]), "r"(a[3]), "r"(blo), "r"(bhi), "r"(sd));
}
__device__ __forceinline__ void wg_rs128t(float (&d)[64], const uint32_t (&a)[4], uint32_t blo, uint32_t bhi, int sd) {
  asm volatile("{\n.reg .pred p;\n.reg .b64 db;\nsetp.ne.b32 p, %70, 0;\nmov.b64 db, {%68, %69};\n"
    "wgmma.mma_async.sync.aligned.m64n128k16.f32.bf16.bf16 {%0,%1,%2,%3,%4,%5,%6,%7,%8,%9,%10,%11,%12,%13,%14,%15,%16,%17,%18,%19,%20,%21,%22,%23,%24,%25,%26,%27,%28,%29,%30,%31,%32,%33,%34,%35,%36,%37,%38,%39,%40,%41,%42,%43,%44,%45,%46,%47,%48,%49,%50,%51,%52,%53,%54,%55,%56,%57,%58,%59,%60,%61,%62,%63}, {%64,%65,%66,%67}, db, p, 1, 1, 1;\n}\n"
    : "+f"(d[0]),"+f"(d[1]),"+f"(d[2]),"+f"(d[3]),"+f"(d[4]),"+f"(d[5]),"+f"(d[6]),"+f"(d[7]),"+f"(d[8]),"+f"(d[9]),"+f"(d[10]),"+f"(d[11]),"+f"(d[12]),"+f"(d[13]),"+f"(d[14]),"+f"(d[15]),"+f"(d[16]),"+f"(d[17]),"+f"(d[18]),"+f"(d[19]),"+f"(d[20]),"+f"(d[21]),"+f"(d[22]),"+f"(d[23]),"+f"(d[24]),"+f"(d[25]),"+f"(d[26]),"+f"(d[27]),"+f"(d[28]),"+f"(d[29]),"+f"(d[30]),"+f"(d[31]),"+f"(d[32]),"+f"(d[33]),"+f"(d[34]),"+f"(d[35]),"+f"(d[36]),"+f"(d[37]),"+f"(d[38]),"+f"(d[39]),"+f"(d[40]),"+f"(d[41]),"+f"(d[42]),"+f"(d[43]),"+f"(d[44]),"+f"(d[45]),"+f"(d[46]),"+f"(d[47]),"+f"(d[48]),"+f"(d[49]),"+f"(d[50]),"+f"(d[51]),"+f"(d[52]),"+f"(d[53]),"+f"(d[54]),"+f"(d[55]),"+f"(d[56]),"+f"(d[57]),"+f"(d[58]),"+f"(d[59]),"+f"(d[60]),"+f"(d[61]),"+f"(d[62]),"+f"(d[63])
    : "r"(a[0]), "r"(a[1]), "r"(a[2]), "r"(a[3]), "r"(blo), "r"(bhi), "r"(sd));
}

__device__ __forceinline__ uint32_t w4(const uint4& v, int i) { return i == 0 ? v.x : i == 1 ? v.y : i == 2 ? v.z : v.w; }

template <bool REMOTE>
__device__ __forceinline__ void kv_process(const uint4& sha, const uint4& shb, int swap, uint32_t base, uint32_t rank, int half, int i, uint32_t ubar) {
    const uint32_t dst = REMOTE ? rank ^ 1 : rank;
    const uint32_t kvs = base + OFF_KV + (half * 4 + (i >> 5)) * 2 * KV_BYTES + (i & 31) * 16 + dst * 8, ks = kvs + (swap ? KV_BYTES : 0), vs = kvs + (swap ? 0 : KV_BYTES);
    uint2 k[8], v[5];
#pragma unroll
    for (int j = 0; j < 8; j++) k[j] = lds64(ks + (j & 3) * 528 + (j >> 2) * 16);
#pragma unroll
    for (int j = 0; j < 5; j++) v[j] = lds64(vs + ((j + 3) & 3) * 528 + ((j + 3) >> 2) * 16);
    uint32_t pw = base + OFF_PW + (8 + 1024 * half + 512 * rank + 4 * i) * 4;
    if (REMOTE) { pw = mapa(pw, dst); ubar = mapa(ubar, dst); }
#pragma unroll
    for (int j = 0; j < 2; j++) {
        const uint4& sh = j ? shb : sha;
        const uint32_t s0 = __byte_perm(sh.x, sh.z, 0x5410), s1 = __byte_perm(sh.x, sh.z, 0x7632);
        const uint32_t s2 = __byte_perm(sh.y, sh.w, 0x5410), s3 = __byte_perm(sh.y, sh.w, 0x7632);
        uint32_t u[5];
#pragma unroll
        for (int r = 0; r < 5; r++)
            u[r] = bmul(badd(badd(badd(bmul(j ? k[r].y : k[r].x, s3), bmul(j ? k[r + 1].y : k[r + 1].x, s2)), bmul(j ? k[r + 2].y : k[r + 2].x, s1)),
                             bmul(j ? k[r + 3].y : k[r + 3].x, s0)), j ? v[r].y : v[r].x);
#pragma unroll
        for (int e = 0; e < 2; e++) {
            const uint32_t sel = e ? 0x7632 : 0x5410;
            const uint32_t w0 = __byte_perm(u[0], u[1], sel), w1 = __byte_perm(u[1], u[2], sel), w2 = __byte_perm(u[2], u[3], sel), w3 = __byte_perm(u[3], u[4], sel);
            if (REMOTE)
                asm volatile("st.async.weak.shared::cluster.mbarrier::complete_tx::bytes.v4.b32 [%0], {%1,%2,%3,%4}, [%5];"
                             ::"r"(pw + (2 * j + e) * PW_PITCH), "r"(w0), "r"(w1), "r"(w2), "r"(w3), "r"(ubar) : "memory");
            else sts128(pw + (2 * j + e) * PW_PITCH, w0, w1, w2, w3);
        }
    }
}
__device__ __forceinline__ void filter_store(const uint4 (&kf)[4], uint32_t base, int half, int i) {
#pragma unroll
    for (int j = 0; j < 4; j++)
        sts128(base + OFF_KB + j * KB_PITCH + (2040 - half * 1024 - 8 * i) * 2, __byte_perm(kf[j].w, 0, 0x1032), __byte_perm(kf[j].z, 0, 0x1032),
               __byte_perm(kf[j].y, 0, 0x1032), __byte_perm(kf[j].x, 0, 0x1032));
}

struct LnStat {
    uint32_t c, rh, rl;
    __device__ __forceinline__ uint32_t operator()(uint32_t x) const { return bfma(x, rh, bfma(x, rl, c)); }
};
__device__ __forceinline__ LnStat ln_stats(const uint32_t (&x)[16], float scale) {
    float s[4], q[4];
#pragma unroll
    for (int i = 0; i < 16; i += 2) {
        const float a = blo(x[i]), b = bhi(x[i]), c = blo(x[i + 1]), d = bhi(x[i + 1]);
        if (i == 0) { s[0] = a; s[1] = b; s[2] = c; s[3] = d; q[0] = a * a; q[1] = b * b; q[2] = c * c; q[3] = d * d; }
        else {
            s[0] += a; s[1] += b; s[2] += c; s[3] += d;
            q[0] = fmaf(a, a, q[0]); q[1] = fmaf(b, b, q[1]); q[2] = fmaf(c, c, q[2]); q[3] = fmaf(d, d, q[3]);
        }
    }
    float s0 = (s[0] + s[1]) + (s[2] + s[3]), q0 = (q[0] + q[1]) + (q[2] + q[3]);
#pragma unroll
    for (int o = 1; o < 16; o <<= 1) { s0 += __shfl_xor_sync(0xffffffffu, s0, o); q0 += __shfl_xor_sync(0xffffffffu, q0, o); }
    const float mean = s0 * (1.0f / 512.f);
    const float var = fmaxf(fmaf(-mean, mean, q0 * (1.0f / 512.f)), 0.f);
    float r;
    asm("rsqrt.approx.ftz.f32 %0, %1;" : "=f"(r) : "f"(var + 1e-5f));
    r *= scale;
    LnStat o;
    const float c = -mean * r;
    o.c = pack2(c, c); o.rh = pack2(r, r);
    const float rl = r - blo(o.rh);
    o.rl = pack2(rl, rl);
    return o;
}

constexpr int NSTAGE = 46;
#define LOOKAHEAD 1860
__host__ __device__ constexpr int st_bytes(int n) { return n >= 16 && n < 32 ? 12288 : STB; }
__host__ __device__ constexpr int st_addr(int n) {
    if (n == 32 || n == 34) return OFF_A + (n - 28) * 8192;
    const int a = (2 + n - (n > 32) - (n > 34)) * STB - (n < 16 ? 0 : n < 32 ? n - 16 : 16) * 4096;
    return OFF_RING + a % (NST * STB);
}
__host__ __device__ constexpr int st_trigger(int n) {
    int m = n - 1, ahead = 0;
    for (;; m--) {
        const int q = (m + NSTAGE) % NSTAGE;
        if (n == 32 || n == 34 ? m == 2 * n - 43 : st_addr(q) < st_addr(n) + st_bytes(n) && st_addr(n) < st_addr(q) + st_bytes(q)) return m;
        ahead += st_bytes(q) / 64;
        if (ahead > LOOKAHEAD) return m;
    }
}
__host__ __device__ constexpr int first_load(int n) { int m = 8; while (st_trigger(m % NSTAGE) + (m >= NSTAGE ? NSTAGE : 0) < n) m++; return m; }
__host__ __device__ constexpr bool monotone() { for (int n = 1; n < NSTAGE; n++) if (st_trigger(n) < st_trigger(n - 1)) return false; return st_trigger(0) + NSTAGE >= st_trigger(NSTAGE - 1); }
static_assert(monotone(), "loads are issued in stream order");
template <int V> struct IC { static constexpr int v = V; };
template <int A, int B, class F> __device__ __forceinline__ void static_for(F&& f) {
    if constexpr (A < B) { f(IC<A>{}); static_for<A + 1, B>(f); }
}
#define SFOR(var, A, B) static_for<A, B>([&](auto _ic) __attribute__((always_inline)) { constexpr int var = decltype(_ic)::v;
#define SEND });
static_assert(st_trigger(7) < 0 && st_trigger(8) >= 0 && st_addr(45) + STB == st_addr(0), "schedule");
struct Stream {
    const CUtensorMap *ma, *mb, *md;
    uint32_t dst, dstb, full;
    int ca, cb, rb, ra, rr, cd, ce, r0, r1, r2;
    __device__ __forceinline__ Stream(const Params& P, uint32_t base, int ps, int rank, int w) {
        ma = &P.wg + (w >> 1); mb = &P.wg + (w < 2 ? w : 2); md = &P.wd;
        dst = base + w * 4096; dstb = dst - (w == 3 ? 2048 : 0); full = base + OFF_BAR + 8 * B_FULL;
        ra = (7 * ps + 4 * rank) * 64; rr = (7 * ps + 4 * (rank ^ 1)) * 64;
        ca = ra + (w & 1) * 64; cd = (4 * rank + w) * 64; ce = (4 * rank + (w >> 1)) * 64;
        r0 = ra + 128 + (w & 1) * 32; r1 = rr + 128 + (w & 1) * 32; r2 = (7 * ps + 3) * 64 + 32 * (rank ^ (w & 1));
        cb = w < 2 ? ra + 128 : 0; rb = w < 2 ? 0 : (2 * ps + rank) * 512 + (w & 1) * 16;
    }
    template <int M> __device__ __forceinline__ void load(bool lead) const {
        constexpr int m = M % NSTAGE;
        constexpr uint32_t so = st_addr(m);
        const uint32_t fb = here(full) + 8 * (m % 23);
        if (lead) mbar_expect_tx(fb, st_bytes(m));
        if constexpr (m < 16) tma2d_w(here(dst) + so, ma, ca, m * 32, fb);
        else if constexpr (m < 32) tma2d_w(here(dstb) + so, mb, cb, here(rb) + (m - 16) * 32, fb);
        else if constexpr (m < 40) tma2d_w(here(dst) + so, md, cd, here(m < 36 ? ra : rr) + (m & 3) * 32, fb);
        else tma2d_w(here(dst) + so, md, here(ce) + (m == 41 || m >= 44 ? 128 : 0), m < 42 ? r0 : (m & 1) ? r2 : r1, fb);
    }
    template <int R> __device__ __forceinline__ void refill(bool lead, bool more_jobs) const {
        SFOR(m, first_load(R), first_load(R + 1))
            if (m < NSTAGE || more_jobs) load<m>(lead);
        SEND
    }
};

template <bool BY_SM> __device__ __forceinline__ int pair_index() {
    if (!BY_SM) return blockIdx.x >> 1;
    uint32_t smid;
    asm volatile("mov.u32 %0, %%smid;" : "=r"(smid));
    const int t = smid >> 1, t7 = ((t - 32) * 37) >> 8;
    const int pa = (t & 7) * 8 + (t >> 3), pb = t * 8 - 55 * t7 - 244, pc = t - 58;
    int pair;
    asm("{\n.reg .pred p, q;\nsetp.lt.s32 p, %1, 32;\nsetp.lt.s32 q, %1, 60;\nselp.s32 %0, %3, %4, q;\nselp.s32 %0, %2, %0, p;\n}"
        : "=&r"(pair) : "r"(t), "r"(pa), "r"(pb), "r"(pc));
    return pair;
}

template <bool BY_SM>
__global__ void __cluster_dims__(2, 1, 1) __launch_bounds__(384, 1) fused_kernel(const __grid_constant__ Params P) {
    extern __shared__ __align__(1024) char smem_raw[];
    uint32_t base = smem_u32(smem_raw);
    asm volatile("mov.u32 %0, %0;" : "+r"(base));
    uint32_t rank;
    asm("mov.u32 %0, %%cluster_ctarank;" : "=r"(rank));
    const int warp = __shfl_sync(0xffffffffu, threadIdx.x >> 5, 0);
    uint32_t smid;
    asm("mov.u32 %0, %%smid;" : "=r"(smid));
    const int pair = pair_index<BY_SM>();
    if (BY_SM && (smid >> 2) == 30) {
        pace(clock(), 4000);
        if (smid == 120 && threadIdx.x == 0) {
            const unsigned target = (__ldcg(&P.cnt[CNT_EPOCH * 32]) + 1) * 128;
            for (unsigned n = 0;; n++) {
                unsigned v;
                asm volatile("ld.relaxed.gpu.global.u32 %0, [%1];" : "=r"(v) : "l"(&P.cnt[CNT_DONE * 32]) : "memory");
                if ((int)(v - target) >= 0) break;
                if (n > SPIN_LIMIT) __trap();
            }
        }
        return;
    }
    if (warp == 0 && elect()) {
        const uint32_t kb = base + OFF_BAR + 8 * B_KV;
#pragma unroll
        for (int i = 0; i < 4; i++) mbar_init(kb + 8 * i, 1);
        asm volatile("fence.mbarrier_init.release.cluster;" ::: "memory");
#pragma unroll
        for (int i = 0; i < 4; i++) {
            mbar_expect_tx(kb + 8 * i, 2 * KV_BYTES);
            tma4d(base + OFF_KV + i * 2 * KV_BYTES, &P.mkv, pair * 8, 128 * rank + 32 * i - 1, kb + 8 * i);
        }
    }
    __syncwarp();
    TRC(threadIdx.x == 0, 144);
    const int role = pair * 2 + rank;
    const int lane = threadIdx.x & 31;
    const int wg = warp >> 2;
    const int tl = threadIdx.x & 127;
    const uint32_t bars = base + OFF_BAR;
#define BAR(i) (here(base) + (OFF_BAR + 8 * (i)))

    auto init_barriers = [&]() {
        if (elect()) {
#pragma unroll
            for (int i = 0; i < 5; i++) mbar_init(bars + (warp + 12 * i) * 8, 1);
            mbar_init(bars + (60 + warp) * 8, 1 + ((0x000113f133c8ull >> (4 * warp)) & 15));
            asm volatile("fence.mbarrier_init.release.cluster;" ::: "memory");
        }
        __syncwarp();
    };

    if (wg < 2) {
        uint4 kf[4], sha, shb;
        uint2 dv;
        if (wg == 1) {
#pragma unroll
            for (int j = 0; j < 4; j++) kf[j] = ldg_nc128((const uint4*)(P.ssmk + (size_t)role * 8192) + tl + j * 256);
            dv = __ldg((const uint2*)(P.ssmd + role * 4));
        }
        {
            const uint4* sp = (const uint4*)(P.shift + (role ^ wg) * 16);
            sha = __ldg(sp); shb = __ldg(sp + 1);
        }
        init_barriers();
        cluster_arrive();
        const int w = warp & 3;
        const bool lead = tl == 0;
        const int myturn = NB_TURN + wg, otherturn = NB_TURN + (wg ^ 1);
        if (wg == 1) {
            if (tl < 32) sts32(base + OFF_PW + (tl >> 3) * PW_PITCH + (tl & 7) * 4, 0);
            else if (tl < 48) sts32(base + OFF_KB + ((tl - 32) >> 2) * KB_PITCH + 4096 + (tl & 3) * 4, 0);
            if (lead) {
                kf[0].x = badd(kf[0].x, 0x80000000u | (dv.x & 0xffffu)); kf[1].x = badd(kf[1].x, 0x80000000u | (dv.x >> 16));
                kf[2].x = badd(kf[2].x, 0x80000000u | (dv.y & 0xffffu)); kf[3].x = badd(kf[3].x, 0x80000000u | (dv.y >> 16));
            }
            filter_store(kf, base, 0, tl);
            fence_async_smem();
            TRC(lead, 16);
        }
        asm volatile("setmaxnreg.inc.sync.aligned.u32 192;");
        cluster_wait();
        {
            const int g = lane >> 2, tig = lane & 3, nb_wg = NB_WG + wg, ps = role >> 5;
            float d[64];
            uint32_t at[2][8][4], aq[8][4];
            float carry[2][2] = {{0.f, 0.f}, {0.f, 0.f}};
            uint32_t spill[2] = {0u, 0u};
            const uint32_t sc = base + OFF_SC + wg * 16384;
            const int wt = w + 3 - tig;
            const uint32_t pwa = base + OFF_PW + wg * 2 * PW_PITCH + (2 + g + 16 * w + 2 * tig) * 4;
            const uint32_t klo = desc_lo(OFF_KB, 16) + wg * (2 * KB_PITCH / 16);
            const uint32_t scw = sc + w * 2048 + g * 4;
            auto load_a = [&](uint32_t (&a)[8][4], uint32_t p) {
#pragma unroll
                for (int j = 0; j < 8; j++) {
                    a[j][0] = lds32(p + j * 512); a[j][1] = lds32(p + j * 512 + 256);
                    a[j][2] = lds32(p + j * 512 + 32); a[j][3] = lds32(p + j * 512 + 288);
                }
            };
#pragma unroll
            for (int part = 0; part < 2; part++) {
                if (part) { sha = lds128(base + OFF_TAG + 16 + wg * 32); shb = lds128(base + OFF_TAG + 32 + wg * 32); }
                else if (lead) { sts128(base + OFF_TAG + 16 + wg * 32, sha.x, sha.y, sha.z, sha.w); sts128(base + OFF_TAG + 32 + wg * 32, shb.x, shb.y, shb.z, shb.w); }
                mbar_wait(part ? BAR(B_KVL) : BAR(B_KV) + 8 * w, 0);
                TRC(tl == 96 && !wg, 145 + part);
                if (wg == 1) {
                    kv_process<true>(sha, shb, P.kv_swap, base, rank, part, tl, BAR(B_UFULL + part));
                    __syncwarp();
                    if (lane == 0) mbar_arrive(BAR(B_UFULL + part));
                } else {
                    kv_process<false>(sha, shb, P.kv_swap, base, rank, part, tl, 0);
                    __syncwarp();
                    if (lane == 0) { mbar_arrive(BAR(B_UFULL + part)); if (part) mbar_arrive_remote(mapa(BAR(B_UFULL + 1), rank ^ 1)); }
                }
                TRC(tl == 96 && !part, 1 + wg * 16);
#pragma unroll
                for (int cc = 0; cc < 2; cc++) {
                    const uint32_t kl = klo + cc * (KB_PITCH / 16);
                    if (part) {
                        if (cc == 0) mbar_wait(BAR(B_K2), 0);
                        nb_sync(myturn, 256);
                        wg_fence();
#pragma unroll
                        for (int j = 0; j < 8; j++) wg_rs128(d, at[cc][j], kl + 16 * j, HI0, j > 0);
                        wg_commit();
                        if (cc == 0) mbar_wait(BAR(B_UFULL + 1), 0);
                        load_a(aq, pwa + cc * PW_PITCH + 4096);
                    } else {
                        if (cc == 0) {
                            mbar_wait(BAR(B_UFULL), 0);
                            TRC(lead, 2 + wg * 16);
                            load_a(at[0], pwa);
                            load_a(at[1], pwa + PW_PITCH);
                        }
#pragma unroll
                        for (int i = 0; i < 32; i++) aq[i >> 2][i & 3] = at[cc][i >> 2][i & 3];
                        if (wg || cc) nb_sync(myturn, 256);
                    }
                    wg_fence();
                    wg_rs128(d, aq[0], kl + 128, HI0, part); wg_rs112(d, aq[1], kl + 144, HI0, 1);
                    wg_rs96(d, aq[2], kl + 160, HI0, 1); wg_rs80(d, aq[3], kl + 176, HI0, 1);
                    wg_rs64(d, aq[4], kl + 192, HI0, 1); wg_rs48(d, aq[5], kl + 208, HI0, 1);
                    wg_rs32(d, aq[6], kl + 224, HI0, 1); wg_rs16(d, aq[7], kl + 240, HI0, 1);
                    wg_commit();
                    nb_arrive(otherturn, 256);
                    wg_wait<0>();
                    pin(d);
                    TRC(lead, 3 + wg * 16 + part * 4 + cc * 2);
                    if (cc && part) {
                        if (wg == 0) { if (lead) mbar_arrive(BAR(B_CONV)); }
                        else {
                            const Stream ws(P, base, ps, rank, w);
                            mbar_wait(BAR(B_CONV), 0);
                            SFOR(m, 4, 8) ws.load<m>(lead); SEND
                            if (!LATEPF && elect()) {
                                const int gam = (role >> 1) & 15;
                                if (w < 2) tma_prefetch2d(ws.mb, ws.cb, gam * 32);
                                if (gam < 14) tma_prefetch2d(ws.md, ws.cd, ps * 448 + gam * 32);
                            }
                            __syncwarp();
                        }
                    }
#pragma unroll
                    for (int i = 0; i < 16; i++) {
                        uint32_t wd = pack2(d[61 - 4 * i] + (i ? d[(67 - 4 * i) & 63] : carry[cc][0]), d[60 - 4 * i] + (i ? d[(66 - 4 * i) & 63] : carry[cc][1]));
                        if (i == 15) {
                            const uint32_t prev = spill[cc];
                            spill[cc] = wd;
                            wd = wt >= 4 ? prev : wd;
                        }
                        sts32(scw + cc * 8192 + ((4 * i + wt) & 63) * 32, wd);
                    }
                    asm volatile("mov.f32 %0, %1;" : "=f"(carry[cc][0]) : "f"(d[3]));
                    asm volatile("mov.f32 %0, %1;" : "=f"(carry[cc][1]) : "f"(d[2]));
                    TRC(lead, 4 + wg * 16 + part * 4 + cc * 2);
                }
                nb_sync(nb_wg, 128);
                float o[2][8];
#pragma unroll
                for (int cc = 0; cc < 2; cc++) {
                    const uint32_t p = sc + cc * 8192 + tl * 16;
                    const uint4 p0 = lds128(p), p1 = lds128(p + 2048), p2 = lds128(p + 4096), p3 = lds128(p + 6144);
#pragma unroll
                    for (int i = 0; i < 4; i++) {
                        o[cc][i] = (blo(w4(p0, i)) + blo(w4(p1, i))) + (blo(w4(p2, i)) + blo(w4(p3, i)));
                        o[cc][4 + i] = (bhi(w4(p0, i)) + bhi(w4(p1, i))) + (bhi(w4(p2, i)) + bhi(w4(p3, i)));
                    }
                }
                const uint32_t tag = lds32(base + OFF_TAG);
                uint32_t* yo = P.yp + (size_t)(part * 128 + (tl & ~1)) * 2048 + (role >> 3) * 128 + (2 * rank + wg) * 32 + (role & 6) * 4 + (tl & 1) * 4;
#pragma unroll
                for (int e = 0; e < 2; e++)
                    *(uint4*)(yo + e * 2048) = make_uint4((pack2(o[0][4 * e], o[1][4 * e]) & ~1u) | tag, (pack2(o[0][4 * e + 1], o[1][4 * e + 1]) & ~1u) | tag,
                                                          (pack2(o[0][4 * e + 2], o[1][4 * e + 2]) & ~1u) | tag, (pack2(o[0][4 * e + 3], o[1][4 * e + 3]) & ~1u) | tag);
                TRC(lead && !part, 12 + wg * 16);
                if (warp == 4) {
                    nb_sync(NB_YS, 256);
                    if (lane == 0) {
                        hint(&P.cnt[(CNT_Y + part) * 32]);
                        mbar_arrive(BAR(B_YD + part));
                        if (part) { mbar_arrive_n(BAR(B_HFREE), 8); mbar_arrive_remote_n(mapa(BAR(B_HFREE), rank ^ 1), 8); }
                    }
                    TRC(lead, 130 + 2 * part);
                    __syncwarp();
                } else nb_arrive(NB_YS, 256);
            }
            if (LATEPF && wg == 1) {
                const Stream ws(P, base, ps, rank, w);
                mbar_wait(BAR(B_AFULL), 0);
                if (elect()) {
                    const int gam = (role >> 1) & 15;
                    if (w < 2) tma_prefetch2d(ws.mb, ws.cb, gam * 32);
                    if (gam < 14) tma_prefetch2d(ws.md, ws.cd, ps * 448 + gam * 32);
                }
                __syncwarp();
            }
            TRC(lead, 11 + wg * 16);
        }
        {
            const int pair2 = pair_index<BY_SM>(), ps = pair2 >> 4;
            const Stream ws(P, base, ps, rank, w);
            constexpr uint32_t alo0 = desc_lo(OFF_A, 16), hlo0 = desc_lo(OFF_R, 16);
#define LANE_VARS() uint32_t lane; asm volatile("mov.u32 %0, %%laneid;" : "=r"(lane)); const uint32_t srow = lane & 15
#define WAITFULL(n) mbar_wait(BAR(B_FULL + (n) % 23), (n) / 23)
#define BDESC(n, lbo) IC<desc_lo(st_addr(n), lbo)>::v
#define REFILL(r) ws.refill<r>(lead, job < 3)
#define STEP(n, k) do { if constexpr ((k) > 1) REFILL((n) - 2); WAITFULL((n) + 1); if constexpr ((k) > 0) wg_wait<1>(); } while (0)
#define STEPL(n) do { nb_arrive(otherturn, 256); REFILL((n) - 2); wg_wait<1>(); REFILL((n) - 1); wg_wait<0>(); REFILL(n); } while (0)
#define READA(c) do { tg0 = lds32(vo + (((c) + 3) & 7) * 8192); tg1 = lds32(vo + (((c) + 3) & 7) * 8192 + 1024); } while (0)
#define CHECKA(c) do { while (__any_sync(0xffffffffu, differ(tg0, tg1, xtag) & 1)) { \
            const uint32_t _rb = BAR(B_RETRY) + 8 * w, _rp = here(base) + OFF_TAG + 96 + 4 * w, _ph = lds32(_rp); \
            if (elect()) mbar_expect_tx(_rb, 2048); \
            fence_async_smem(); __syncwarp(); \
            tma2d_w(here(base) + OFF_A + (((c) + 3) & 7) * 8192 + w * 2048, &P.xr, (c) * 64, ((pair2 & 15) + 16 * jp) * 64 + 16 * w, _rb); \
            mbar_wait(_rb, _ph); sts32(_rp, _ph ^ 1); RETRY_COUNT(); READA(c); } } while (0)
#define ACH(c) (alo0 + ((((c) + 3) & 7) << 9))
#define STAGE256(n, alo, ahi, acc) do { const uint32_t _b = BDESC(n, 4096), _a = (alo); wg_fence(); \
        wg_ss256<0>(d, _a, ahi, _b, HI128, acc); wg_ss256<0>(d, _a + 2, ahi, _b + 128, HI128, 1); wg_commit(); } while (0)
#define STAGE192(n, alo, acc) do { const uint32_t _b = BDESC(n, 4096), _a = (alo); wg_fence(); \
        wg_ss192<0>(db, _a, HI128, _b, HI128, acc); wg_ss192<0>(db, _a + 2, HI128, _b + 128, HI128, 1); wg_commit(); } while (0)
#pragma unroll 1
            for (int job = 0; job < 4; job++) {
                const uint32_t jp = job & 1;
                if ((int)jp == wg) {
                    float d[128];
                    const uint32_t xtag = job < 2;
                    uint32_t vo, tg0, tg1;
                    { LANE_VARS(); (void)srow; vo = base + OFF_A + w * 2048 + (lane >> 2) * 128 + (((2 * (lane & 3)) ^ (lane >> 2)) << 4) + (lane >> 3) * 4; }
                    mbar_wait(BAR(B_AFULL), jp);
                    nb_sync(myturn, 256);
                    WAITFULL(0);
                    TRC(lead, 32 + job * 16);
                    SFOR(c, 0, 8)
                        STAGE256(2 * c, ACH(c), HI128, c > 0);
                        if constexpr (c >= 4 && c < 7) mbar_wait(BAR(B_ALAND + c + 1), jp);
                        STEP(2 * c, 2 * c);
                        if constexpr (c >= 4 && c < 7) READA(c + 1);
                        STAGE256(2 * c + 1, ACH(c) + 4, HI128, 1);
                        if constexpr (c < 7) {
                            if constexpr (c > 0) REFILL(2 * c - 1);
                            if constexpr (c < 4) mbar_wait(BAR(B_AFULL + c + 1), jp);
                            else CHECKA(c + 1);
                            STEP(2 * c + 1, 1);
                        }
                    SEND
                    STEPL(15);
                    pin(d);
                    if (lead) { mbar_arrive(BAR(B_AEMPTY)); mbar_arrive_remote(mapa(BAR(B_AEMPTY), rank ^ 1)); }
                    TRC(lead, 33 + job * 16);
                    uint32_t ha[8][4];
#pragma unroll
                    for (int i = 0; i < 32; i++) ha[i >> 2][i & 3] = pack2(glu(d[2 * i], d[64 + 2 * i]), glu(d[2 * i + 1], d[65 + 2 * i]));
                    mbar_wait(BAR(B_HFREE), jp);
                    {
                        LANE_VARS();
                        const uint32_t hrow = base + OFF_R + H_AOWN + (16 * w + srow) * 128;
                        const uint32_t src = base + OFF_R + H_AOWN + w * 2048, dst = mapa(base + OFF_R + H_AREM + w * 2048, rank ^ 1), rb = mapa(BAR(B_HAREM), rank ^ 1);
#pragma unroll
                        for (int i = 0; i < 8; i++) {
                            stsm4(hrow + (i >> 2) * 8192 + ((((2 * i & 7) + (lane >> 4)) ^ (lane & 7)) << 4), ha[i][0], ha[i][1], ha[i][2], ha[i][3]);
                        }
                        fence_async_smem();
                        __syncwarp();
                        const uint32_t t0 = clock();
#pragma unroll
                        for (int i = 0; i < 2; i++) {
                            pace(t0, (4 * i + w) * PACE_H);
                            if (elect()) bulk_s2s(dst + i * 8192, src + i * 8192, 2048, rb);
                        }
                    }
                    TRC(lead, 34 + job * 16);
                    float o0[64], o1[64];
                    nb_sync(myturn, 256);
                    WAITFULL(32);
                    TRC(lead, 35 + job * 16);
                    SFOR(c, 0, 4)
                        const uint32_t b_ = BDESC(32 + c, 4096);
                        wg_fence();
                        wg_rs128t(o0, ha[2 * c], b_, HI128, c > 0); wg_rs128t(o1, ha[2 * c], b_ + 512, HI128, c > 0);
                        wg_rs128t(o0, ha[2 * c + 1], b_ + 128, HI128, 1); wg_rs128t(o1, ha[2 * c + 1], b_ + 640, HI128, 1);
                        wg_commit();
                        if constexpr (c == 3) mbar_wait(BAR(B_HAREM), jp);
                        STEP(32 + c, c);
                    SEND
                    SFOR(c, 0, 4)
                        const uint32_t b_ = BDESC(36 + c, 4096), a_ = hlo0 + (H_AREM >> 4) + (c >> 1) * 512 + (c & 1) * 4;
                        wg_fence();
                        wg_ss128<0>(o0, a_, HI128, b_, HI128, 1); wg_ss128<0>(o1, a_, HI128, b_ + 512, HI128, 1);
                        wg_ss128<0>(o0, a_ + 2, HI128, b_ + 128, HI128, 1); wg_ss128<0>(o1, a_ + 2, HI128, b_ + 640, HI128, 1);
                        wg_commit();
                        if (c == 0 && lead) {
                            mbar_arrive_remote(mapa(BAR(B_HACK), rank ^ 1));
                            if (job < 3) { mbar_arrive(BAR(B_ATMP)); mbar_arrive_remote(mapa(BAR(B_ATMP), rank ^ 1)); }
                        }
                        if constexpr (c == 3) mbar_wait(BAR(B_HBOWN), jp);
                        STEP(36 + c, 2);
                    SEND
#define STAGE128(n, o, c) do { const uint32_t _b = BDESC(n, 8192), _a = hlo0 + (H_BOWN >> 4) + (c) * 512, _a2 = _a + ((c) == 2 ? 256 : 4); \
        constexpr uint32_t _hi = (c) == 2 ? HI64 : HI128; wg_fence(); \
        wg_ss128<0>(o, _a, _hi, _b, HI128, 1); wg_ss128<0>(o, _a + 2, _hi, _b + 128, HI128, 1); \
        wg_ss128<0>(o, _a2, _hi, _b + 256, HI128, 1); wg_ss128<0>(o, _a2 + 2, _hi, _b + 384, HI128, 1); wg_commit(); } while (0)
#define STAGE_OUT(o, grp) do { const uint32_t _r = here(base) + OFF_R + w * 8192 + (grp) * 2048 + srow * 128; \
        _Pragma("unroll") for (int i = 0; i < 8; i += 2) { const int k = ((grp) & 1) * 32 + 4 * i; \
            stsm4(_r + (((i + (lane >> 4)) ^ (lane & 7)) << 4), (pack2(o[k], o[k + 1]) & am) | om, (pack2(o[k + 2], o[k + 3]) & am) | om, \
                  (pack2(o[k + 4], o[k + 5]) & am) | om, (pack2(o[k + 6], o[k + 7]) & am) | om); } \
        if (job == 3) nb_arrive(NB_FIN + (grp), 256); } while (0)
                    STAGE128(40, o0, 0);
                    STEP(40, 2);
                    STAGE128(41, o1, 0);
                    mbar_wait(BAR(B_HBREM), jp);
                    STEP(41, 2);
                    STAGE128(42, o0, 1);
                    STEP(42, 2);
                    STAGE128(43, o0, 2);
                    mbar_wait(BAR(B_HACK), jp);
                    STEP(43, 2);
                    STAGE128(44, o1, 1);
                    STEP(44, 2);
                    STAGE128(45, o1, 2);
                    if (job < 3) nb_arrive(otherturn, 256);
                    else if (lead) hint(&P.cnt[CNT_DONE * 32]);
                    REFILL(43);
                    pin(o0);
                    LANE_VARS();
                    const bool tagged = job < 2 && (lane & 3) == 0;
                    const uint32_t am = tagged ? ~1u : ~0u, om = tagged ? lds32(base + OFF_TAG) : 0u;
                    STAGE_OUT(o0, 0);
                    wg_wait<1>();
                    REFILL(44);
                    wg_wait<0>();
                    REFILL(45);
                    pin(o1);
                    if (lead && job < 3) {
                        mbar_arrive(BAR(B_P2DONE)); mbar_arrive_remote(mapa(BAR(B_P2DONE), rank ^ 1));
                        mbar_expect_tx(BAR(B_HAREM), 16384); mbar_expect_tx(BAR(B_HBREM), 12288);
                    }
                    TRC(lead, 36 + job * 16);
                    {
                        const int k = (w - ps - 1) & 3, row = ((pair2 & 15) + 16 * jp) * 64 + 16 * w;
                        const uint32_t dt = job < 2 ? PACE : PACE3, np = job < 2 ? 3 : job == 2 ? 4 : 0;
                        uint32_t t0 = clock() + k * dt;
                        const bool send = k < (int)np, l1 = job < 2;
                        unsigned* hp = &P.cnt[(CNT_P + (row >> 4)) * 32];
                        auto piece = [&](int i) {
                            if (send) {
                                const uint32_t src = here(base) + OFF_R + w * 8192 + i * 2048;
                                wait_until(t0);
                                if (l1) tma_store3d_w(&P.f, row, k * 8 + 4 * rank + i, src);
                                else tma_red3d_w(&P.out, row, 4 * rank + i, src);
                                t0 += np * dt;
                            }
                        };
                        if (send) { fence_async_smem(); __syncwarp(); }
                        piece(0);
                        STAGE_OUT(o0, 1);
                        if (send) { fence_async_smem(); __syncwarp(); }
                        piece(1);
                        STAGE_OUT(o1, 2);
                        STAGE_OUT(o1, 3);
                        fence_async_smem();
                        __syncwarp();
                        piece(2);
                        piece(3);
                        if (HNOW && send && l1 && lane == 0) hint(hp);
                        if (elect()) {
                            if (job < 2 && k == 3) { mbar_arrive(BAR(B_OWN)); mbar_arrive_remote(mapa(BAR(B_OWN), rank ^ 1)); }
                            bulk_commit();
                            bulk_wait_read();
                            if (!HNOW && send && l1) hint(hp);
                            if (job < 3) { mbar_arrive(BAR(B_HFREE)); mbar_arrive_remote(mapa(BAR(B_HFREE), rank ^ 1)); }
                        }
                        __syncwarp();
                    }
                    TRC(lead, 37 + job * 16);
                } else {
                    float db[96];
                    nb_sync(myturn, 256);
                    WAITFULL(16);
                    TRC(lead, 40 + job * 16);
                    SFOR(c, 0, 16)
                        STAGE192(16 + c, ACH(c >> 1) + (c & 1) * 4, c > 0);
                        if constexpr (c < 15) STEP(16 + c, c);
                    SEND
                    STEPL(31);
                    pin(db);
                    if (lead) { mbar_arrive(BAR(B_AEMPTY)); mbar_arrive_remote(mapa(BAR(B_AEMPTY), rank ^ 1)); }
                    TRC(lead, 41 + job * 16);
                    {
                        uint32_t r[24];
#pragma unroll
                        for (int i = 0; i < 16; i++) r[i] = pack2(glu(db[2 * i], db[32 + 2 * i]), glu(db[2 * i + 1], db[33 + 2 * i]));
                        mbar_wait(BAR(B_AEMPTY), jp);
                        LANE_VARS();
                        const uint32_t hrow = base + OFF_R + H_BOWN + (16 * w + srow) * 128;
                        const uint32_t hrow2 = base + OFF_R + H_HOWN + (16 * w + srow) * 64;
                        const uint32_t rb = mapa(BAR(B_HBREM), rank ^ 1);
#pragma unroll
                        for (int i = 0; i < 8; i += 2) stsm4(hrow + (((i + (lane >> 4)) ^ (lane & 7)) << 4), r[2 * i], r[2 * i + 1], r[2 * i + 2], r[2 * i + 3]);
                        fence_async_smem();
                        __syncwarp();
                        const uint32_t t0 = clock();
                        pace(t0, w * PACE_H);
                        if (elect()) bulk_s2s(mapa(base + OFF_R + H_BREM + w * 2048, rank ^ 1), base + OFF_R + H_BOWN + w * 2048, 2048, rb);
#pragma unroll
                        for (int i = 0; i < 8; i++) r[16 + i] = pack2(glu(db[64 + 2 * i], db[80 + 2 * i]), glu(db[65 + 2 * i], db[81 + 2 * i]));
#pragma unroll
                        for (int i = 0; i < 4; i += 2) stsm4(hrow2 + (((i + (lane >> 4)) ^ ((lane >> 1) & 3)) << 4), r[16 + 2 * i], r[17 + 2 * i], r[18 + 2 * i], r[19 + 2 * i]);
                        fence_async_smem();
                        __syncwarp();
                        if (elect()) {
                            bulk_s2s(mapa(base + OFF_R + H_HREM + w * 1024, rank ^ 1), base + OFF_R + H_HOWN + w * 1024, 1024, rb);
                            mbar_arrive(BAR(B_HBOWN));
                        }
                        __syncwarp();
                    }
                    TRC(lead, 42 + job * 16);
                }
            }
        }
    } else {
        unsigned epoch;
        asm volatile("ld.global.cg.u32 %0, [%1];" : "=r"(epoch) : "l"(&P.cnt[CNT_EPOCH * 32]));
        if (tl < 10) prefetch_tmap(&P.wg + tl);
        init_barriers();
        cluster_arrive();
        asm volatile("setmaxnreg.dec.sync.aligned.u32 120;");
        if ((base & 0x3FFFF) != SMEM0) __trap();
        const int ps = pair >> 4, gam = pair & 15;
        cluster_wait();
        const int wl = warp & 3, l16 = lane & 15;
        const int rw = ps * 16 + 8 * rank + 2 * wl;
        const uint32_t xo = (gam * 64 + rw + (lane >> 4)) * 512 + l16 * 8;
        const uint32_t tag = (epoch + 1) & 1;
        uint32_t x[16], y[16], yk[16], qr = 0, qc = 0, qrk = 0, qck = 0;
        if (wl == 3) { sts128(base + OFF_ZERO + lane * 16, 0, 0, 0, 0); sts128(base + OFF_ZERO + 512 + lane * 16, 0, 0, 0, 0); }
        {
            const Stream ws(P, base, ps, rank, wl);
            const uint32_t aux = base + OFF_A + wl * 2048, ab = BAR(B_AUX + wl);
            if (lane == 0) {
                sts32(base + OFF_TAG, tag);
                sts32(base + OFF_TAG + 96 + 4 * wl, 0);
                mbar_expect_tx(wl < 2 ? BAR(B_UFULL) + 8 * wl : BAR(B_HAREM - 2) + 8 * wl, wl < 2 ? 8192 : wl == 2 ? 16384 : 12288);
            }
            __syncwarp();
            if (warp == 11) {
                const uint32_t pk = base + OFF_A + 7 * 8192;
                if (elect()) {
                    const int hc = (7 * (role >> 5) + 3) * 64 + ((role >> 4) & 1) * 32, hr = (role & 15) * 32;
                    mbar_expect_tx(BAR(B_PACK), 4096);
                    tma2d(pk, &P.hg, hc, hr, BAR(B_PACK));
                    tma2d(pk + 2048, &P.hu, hc, hr, BAR(B_PACK));
                    mbar_expect_tx(BAR(B_KVL), 8 * KV_BYTES);
#pragma unroll 1
                    for (int i = 0; i < 4; i++) tma4d(base + OFF_KV + (4 + i) * 2 * KV_BYTES, &P.mkv, pair * 8, 256 + 128 * rank + 32 * i - 1, BAR(B_KVL));
                }
                __syncwarp();
            }
            nb_sync(NB_LN, 128);
            if (elect()) {
                mbar_expect_tx(ab, 4096);
                bulk_g2s(aux + 6 * 8192, P.ssmk + (size_t)(role * 4 + wl) * 2048 + 1024, 2048, ab);
                bulk_g2s(aux + 5 * 8192, P.q + (size_t)(gam * 64 + rw) * 512, 2048, ab);
            }
            __syncwarp();
            if (PREFILL == 0) { SFOR(m, 0, 4) ws.load<m>(tl == 0); SEND }
            if (wl == 3) {
                mbar_wait(BAR(B_PACK), 0);
                mbar_wait(BAR(B_UFULL), 0);
                pace(clock(), 200);
                if (elect()) {
                    tma_store2d(&P.hp, 0, role * 32, base + OFF_A + 7 * 8192);
                    tma_store2d(&P.hp, 32, role * 32, base + OFF_A + 7 * 8192 + 2048);
                    bulk_commit();
                    bulk_wait();
                    release(&P.cnt[CNT_W * 32]);
                }
                __syncwarp();
            }
            mbar_wait(ab, 0);
            if (PREFILL == 1) { SFOR(m, 0, 4) ws.load<m>(tl == 0); SEND }
            if (elect()) {
                tma_prefetch2d(ws.ma, ws.ca, gam * 32);
                bulk_prefetch(P.q + (size_t)(1024 + gam * 64 + rw) * 512, 2048);
            }
#pragma unroll
            for (int j = 0; j < 4; j++) {
                const uint4 v = lds128(aux + 6 * 8192 + (j * 32 + lane) * 16);
                sts128(base + OFF_KB + wl * KB_PITCH + (1016 - 8 * (j * 32 + lane)) * 2, __byte_perm(v.w, 0, 0x1032), __byte_perm(v.z, 0, 0x1032),
                       __byte_perm(v.y, 0, 0x1032), __byte_perm(v.x, 0, 0x1032));
            }
            fence_async_smem();
            __syncwarp();
            if (lane == 0) mbar_arrive(BAR(B_K2));
#pragma unroll
            for (int j = 0; j < 4; j++) {
                const uint4 v = lds128(aux + 5 * 8192 + (lane >> 4) * 1024 + j * 256 + l16 * 16);
                x[4 * j] = v.x; x[4 * j + 1] = v.y; x[4 * j + 2] = v.z; x[4 * j + 3] = v.w;
            }
            TRC(tl == 0, 100);
        }
#pragma unroll
        for (int i = 0; i < 16; i++) y[i] = yk[i] = 0;
        uint32_t lph = 0;
#pragma unroll 1
        for (int task = 0; task < 4; task++) {
            const int tile = gam + 16 * (task & 1);
            const uint32_t to = (task & 1) * (1024 * 512);
            if (task >= 2) {
#pragma unroll
                for (int i = 0; i < 16; i++) x[i] = bfma(bfma(x[i], qr, qc), y[i], x[i]);
                const uint32_t r16 = (rw & 15) + (lane >> 4);
                const uint32_t oa = base + OFF_R + ps * 8192 + (l16 >> 3) * 2048 + r16 * 128 + (((l16 ^ r16) & 7) << 4);
                mbar_wait(BAR(B_OWN), task & 1);
                uint4 v[12];
#pragma unroll
                for (int j = 0; j < 4; j++)
                    asm volatile("ld.shared::cluster.v4.u32 {%0,%1,%2,%3}, [%4];" : "=r"(v[j].x), "=r"(v[j].y), "=r"(v[j].z), "=r"(v[j].w)
                                 : "r"(mapa(oa + (j & 1) * 4096, j >> 1)) : "memory");
#pragma unroll
                for (int i = 0; i < 16; i++) x[i] = badd(x[i], w4(v[i >> 2], i & 3));
                sts32(base + OFF_TBL, x[3] ^ x[7] ^ x[11] ^ x[15]);
                __syncwarp();
                if (lane == 0) { mbar_arrive(BAR(B_HFREE)); mbar_arrive_remote(mapa(BAR(B_HFREE), rank ^ 1)); }
                __syncwarp();
                poll(&P.cnt[(CNT_P + tile * 4 + ps) * 32], (epoch + 1) * 6);
                TRC(tl == 0, 101 + task * 4);
                TRC(lane == 0, 210 + task * 4 + wl);
                const __nv_bfloat16* src = P.fp + 3 * (to + xo) - l16 * 16;
                uint32_t bad;
                do {
#pragma unroll
                    for (int i = 0; i < 12; i++)
                        asm volatile("ld.relaxed.gpu.global.v4.u32 {%0,%1,%2,%3}, [%4];" : "=r"(v[i].x), "=r"(v[i].y), "=r"(v[i].z), "=r"(v[i].w) : "l"(src + i * 128) : "memory");
                    bad = 0;
#pragma unroll
                    for (int i = 0; i < 12; i += 2) bad |= differ(v[i].x, v[i + 1].x, tag);
                } while (__any_sync(0xffffffffu, bad & 1));
#pragma unroll
                for (int i = 0; i < 16; i++) x[i] = badd(badd(x[i], w4(v[i >> 2], i & 3)), badd(w4(v[4 + (i >> 2)], i & 3), w4(v[8 + (i >> 2)], i & 3)));
            }
            uint4 qn[4];
            auto load_qn = [&]() {
#pragma unroll
                for (int j = 0; j < 4; j++) qn[j] = ldg_nc128(P.q + (to ^ (1024 * 512)) + xo + j * 128);
            };
            TRD(x[15], 150 + task * 4);
            LnStat l1 = ln_stats(x, 1.0f);
            TRD(l1.rh, 151 + task * 4);
            if (task < 2) {
                if (task == 1 && wl == 3) {
                    mbar_wait(BAR(B_AFULL + 2), 0);
                    uint32_t t0 = clock();
                    __nv_bfloat16* zp = P.o + (size_t)(gam * 64 + ps * 16 + 8 * rank) * 512;
#pragma unroll 1
                    for (int i = 0; i < 16; i++) {
                        wait_until(t0);
                        if (elect()) bulk_s2g(zp + (i & 7) * 512 + (i >> 3) * (1024 * 512), base + OFF_ZERO, 1024);
                        __syncwarp();
                        t0 += ZPACE;
                    }
                } else if (wl == (task ? 0 : 2)) {
                    mbar_wait(BAR(B_YD) + 8 * task, 0);
                    poll(&P.cnt[(CNT_Y + task) * 32], (epoch + 1) * 128);
                    if (lane == 0) mbar_arrive(BAR(B_Y1 - 1) + 8 * task);
                }
                mbar_wait(BAR(B_Y1 - 1) + 8 * task, 0);
                TRC(tl == 0, 101 + task * 4);
                const uint32_t* yp = P.yp + (size_t)((tile * 4 + ps) * 2 + rank) * 2048 + (l16 >> 2) * 128 + (l16 & 3) * 8 + 2 * wl + (lane >> 4);
#pragma unroll
                for (int i = 0; i < 16; i++) asm volatile("ld.global.ca.u32 %0, [%1];" : "=r"(y[i]) : "l"(yp + (i >> 2) * 512 + (i & 3) * 32) : "memory");
                while (true) {
                    uint32_t bad = 0;
#pragma unroll
                    for (int i = 0; i < 16; i += 2) bad |= differ(y[i], y[i + 1], tag);
                    if (!__any_sync(0xffffffffu, bad & 1)) break;
#pragma unroll
                    for (int i = 0; i < 16; i++) asm volatile("ld.relaxed.gpu.global.u32 %0, [%1];" : "=r"(y[i]) : "l"(yp + (i >> 2) * 512 + (i & 3) * 32) : "memory");
                }
            }
#pragma unroll
            for (int i = 0; i < 16; i++) x[i] = bfma(bfma(x[i], l1.rh, l1.c), y[i], x[i]);
            TRD(x[15], 152 + task * 4);
            const LnStat l2 = ln_stats(x, 0.5f);
            TRD(l2.rl, 153 + task * 4);
            const uint32_t xtag = task < 2;
            {
                const uint32_t tm = (lane & 1) ? 0u : 1u << wl;
                auto tg = [&](int i) { const uint32_t m = (tm >> (i & 3)) & 1; return (l2(x[i]) & ~m) | (xtag & m); };
#pragma unroll
                for (int j = 0; j < 4; j++) *(uint4*)(P.xnp + to + xo + j * 128) = make_uint4(tg(4 * j), tg(4 * j + 1), tg(4 * j + 2), tg(4 * j + 3));
                TRC(tl == 0, 102 + task * 4);
                if (XDEL) pace(clock(), XDEL);
                if (lane == 0) hint(&P.cnt[(CNT_X + tile) * 32]);
                __syncwarp();
            }
            TRC(tl == 0, 103 + task * 4);
            TRC(lane == 0, 190 + task * 4 + wl);
            if (task) load_qn();
            else qn[0] = qn[1] = qn[2] = qn[3] = make_uint4(0, 0, 0, 0);
            const int ar = tile * 64;
            if (wl == 0) {
                const uint32_t pa = task ? PACE_A : PACE_A0, tpub = clock();
                auto load_chunk = [&](int c) { if (elect()) tma2d_mc(base + OFF_A + ((c + 3) & 7) * 8192, &P.xn, c * 64, ar, BAR(B_ALAND) + 8 * c); __syncwarp(); };
                mbar_wait(task ? BAR(B_ATMP) : BAR(B_UFULL + 1), task ? (task - 1) & 1 : 0);
                if (lane < 8) mbar_expect_tx(BAR(B_ALAND) + 8 * lane, 8192);
                if (SPEC && task >= 2) {
                    wait_until(tpub + SDELAY);
                    tma2d_w(base + OFF_A + 3 * 8192, &P.xn, 0, ar, BAR(B_ALAND));
                    if (SPEC > 1) { wait_until(tpub + SDELAY + SDELAY2); tma2d_w(base + OFF_A + 4 * 8192, &P.xn, 64, ar, BAR(B_ALAND + 1)); }
                }
                poll(&P.cnt[(CNT_X + tile) * 32], epoch * 64 + 32 + 32 * (task >> 1));
                if (!SPEC || task < 2) tma2d_w(base + OFF_A + 3 * 8192, &P.xn, 0, ar, BAR(B_ALAND));
                TRC(tl == 0, 120 + task * 2);
                uint32_t t0 = clock() - (task >= 2 ? SPEC * pa : 0);
                pace(t0, (2 - rank) * pa);
                if (SPEC < 2 || task < 2 || rank == 0) load_chunk(2 - rank);
                pace(t0, (4 - rank) * pa);
                load_chunk(4 - rank);
                if (task) mbar_wait(BAR(B_P2DONE), (task - 1) & 1);
                else mbar_wait(BAR(B_W), 0);
                t0 = clock();
                pace(t0, (1 - rank) * PACE_B);
                load_chunk(6 - rank);
                if (rank) { pace(t0, 2 * PACE_B); load_chunk(7); }
                TRC(tl == 0, 121 + task * 2);
            } else if (wl < 3) {
                const uint32_t vo = (lane >> 2) * 128 + (((2 * (lane & 3)) ^ (lane >> 2)) << 4) + (lane >> 3) * 4;
#pragma unroll 1
                for (int c = wl - 1; c < 5;) {
                    const uint32_t ca = base + OFF_A + ((c + 3) & 7) * 8192;
                    mbar_wait(BAR(B_ALAND) + 8 * c, (lph >> c) & 1);
                    lph ^= 1u << c;
                    uint32_t tw[8], bad = 0;
#pragma unroll
                    for (int i = 0; i < 8; i++) tw[i] = lds32(ca + vo + i * 1024);
#pragma unroll
                    for (int i = 0; i < 8; i += 2) bad |= differ(tw[i], tw[i + 1], xtag);
                    if (__any_sync(0xffffffffu, bad & 1)) {
                        if (lane == 0) mbar_expect_tx(BAR(B_ALAND) + 8 * c, 8192);
                        fence_async_smem();
                        __syncwarp();
                        tma2d_w(ca, &P.xn, c * 64, ar, BAR(B_ALAND) + 8 * c);
                    } else {
                        if (lane == 0) mbar_arrive(BAR(B_AFULL) + 8 * c);
                        c += 2;
                    }
                }
            } else {
                if (task == 0) { poll(&P.cnt[CNT_W * 32], (epoch + 1) * 128); fence_async_global(); if (lane == 0) mbar_arrive(BAR(B_W)); __syncwarp(); }
                if (task == 1) { if (elect()) { bulk_commit(); bulk_wait(); release(&P.cnt[(CNT_Z + gam) * 32]); } __syncwarp(); }
                if (task == 2) { poll(&P.cnt[(CNT_Z + gam) * 32], (epoch + 1) * 8); fence_async_global(); }
            }
            if (task == 3) break;
            if (task == 0) { mbar_wait(BAR(B_AFULL), 0); load_qn(); }
#pragma unroll
            for (int i = 0; i < 16; i++) {
                const uint32_t t = yk[i] ^ y[i];
                y[i] = task == 2 ? t : yk[i];
                yk[i] = task == 2 ? x[i] : t;
                x[i] = w4(qn[i >> 2], i & 3);
            }
            qr = qrk; qc = qck; qrk = l1.rh; qck = l1.c;
        }
        mbar_wait(BAR(B_P2DONE), 0);
        if (lane == 0) { mbar_arrive(BAR(B_HFREE)); mbar_arrive_remote(mapa(BAR(B_HFREE), rank ^ 1)); }
        __syncwarp();
        if (role == 0 && tl == 0) P.cnt[CNT_EPOCH * 32] = epoch + 1;
        {
            mbar_wait(BAR(B_HFREE), 1);
            const uint32_t t0 = clock();
#pragma unroll
            for (int j = 0; j < 8; j++) {
                const uint32_t (&v)[16] = j < 4 ? yk : x;
                const int i = (j & 3) * 4;
                pace(t0, j * XPACE);
                asm volatile("red.global.add.noftz.v4.bf16x2 [%0], {%1,%2,%3,%4};" ::"l"(P.o + (j >> 2) * (1024 * 512) + xo + (j & 3) * 128), "r"(v[i]), "r"(v[i + 1]), "r"(v[i + 2]), "r"(v[i + 3]) : "memory");
            }
        }
#pragma unroll 1
        for (int i = 0; i < 4; i++) {
            nb_sync(NB_FIN + i, 256);
            const uint32_t src = base + OFF_R + wl * 8192 + i * 2048 + lds32(base + OFF_ZERO);
            fence_async_smem();
            tma_red3d_w(&P.out, (gam + 16) * 64 + 16 * wl, 4 * rank + i, src);
        }
        if (elect()) { bulk_commit(); bulk_wait_read(); }
        __syncwarp();
    }
    TRC(threadIdx.x == 288, 140);
    cluster_arrive();
    cluster_wait();
}

typedef CUresult (*EncodeFn)(CUtensorMap*, CUtensorMapDataType, cuuint32_t, void*, const cuuint64_t*, const cuuint64_t*, const cuuint32_t*,
                             const cuuint32_t*, CUtensorMapInterleave, CUtensorMapSwizzle, CUtensorMapL2promotion, CUtensorMapFloatOOBfill);

void enc2(EncodeFn fn, CUtensorMap* tm, const void* p, int cols, int rows, int bc, int br, CUtensorMapSwizzle sw) {
    cuuint64_t dims[2] = {(cuuint64_t)cols, (cuuint64_t)rows}, strides[1] = {(cuuint64_t)cols * 2};
    cuuint32_t box[2] = {(cuuint32_t)bc, (cuuint32_t)br}, es[2] = {1, 1};
    fn(tm, CU_TENSOR_MAP_DATA_TYPE_BFLOAT16, 2, (void*)p, dims, strides, box, es, CU_TENSOR_MAP_INTERLEAVE_NONE, sw, CU_TENSOR_MAP_L2_PROMOTION_L2_128B, CU_TENSOR_MAP_FLOAT_OOB_FILL_NONE);
}
void enc3(EncodeFn fn, CUtensorMap* tm, const void* p, int cols, int rows, int br, int bg, int gw = 64) {
    cuuint64_t dims[3] = {(cuuint64_t)gw, (cuuint64_t)rows, (cuuint64_t)(cols / gw)}, strides[2] = {(cuuint64_t)cols * 2, (cuuint64_t)gw * 2};
    cuuint32_t box[3] = {(cuuint32_t)gw, (cuuint32_t)br, (cuuint32_t)bg}, es[3] = {1, 1, 1};
    fn(tm, CU_TENSOR_MAP_DATA_TYPE_BFLOAT16, 3, (void*)p, dims, strides, box, es, CU_TENSOR_MAP_INTERLEAVE_NONE,
       gw == 64 ? CU_TENSOR_MAP_SWIZZLE_128B : CU_TENSOR_MAP_SWIZZLE_64B, CU_TENSOR_MAP_L2_PROMOTION_L2_128B, CU_TENSOR_MAP_FLOAT_OOB_FILL_NONE);
}

}

extern "C" void kernel_launch(void* const* d_in, const int* in_sizes, int n_in, void* d_out, int out_size) {
    void* fnp = nullptr;
    cudaDriverEntryPointQueryResult st;
    cudaGetDriverEntryPoint("cuTensorMapEncodeTiled", &fnp, cudaEnableDefault, &st);
    EncodeFn fn = (EncodeFn)fnp;
    void *py, *pxn, *pcnt;
    cudaGetSymbolAddress(&py, g_y);
    cudaGetSymbolAddress(&pxn, g_xn);
    cudaGetSymbolAddress(&pcnt, g_cnt);
    Params P;
    P.q = (const __nv_bfloat16*)d_in[0];
    P.shift = (const __nv_bfloat16*)d_in[3]; P.ssmk = (const __nv_bfloat16*)d_in[4]; P.ssmd = (const __nv_bfloat16*)d_in[5];
    P.o = (__nv_bfloat16*)d_out; P.xnp = (__nv_bfloat16*)pxn; P.yp = (uint32_t*)py; P.cnt = (unsigned*)pcnt;
    P.trace = nullptr;
    {
        char *pk = (char*)d_in[1], *pv = (char*)d_in[2];
        P.kv_swap = pv < pk;
        cuuint64_t dims[4] = {512, 512, 4, 2}, strides[3] = {4096, 1024, (cuuint64_t)(P.kv_swap ? pk - pv : pv - pk)};
        cuuint32_t box[4] = {8, 33, 4, 2}, es[4] = {1, 1, 1, 1};
        fn(&P.mkv, CU_TENSOR_MAP_DATA_TYPE_BFLOAT16, 4, P.kv_swap ? pv : pk, dims, strides, box, es, CU_TENSOR_MAP_INTERLEAVE_NONE, CU_TENSOR_MAP_SWIZZLE_NONE,
           CU_TENSOR_MAP_L2_PROMOTION_L2_128B, CU_TENSOR_MAP_FLOAT_OOB_FILL_NONE);
    }
    enc2(fn, &P.wg, d_in[7], 1792, 512, 64, 32, CU_TENSOR_MAP_SWIZZLE_128B);
    enc2(fn, &P.wu, d_in[8], 1792, 512, 64, 32, CU_TENSOR_MAP_SWIZZLE_128B);
    void* pwp;
    cudaGetSymbolAddress(&pwp, g_wp);
    enc2(fn, &P.wp, pwp, 64, 4096, 64, 16, CU_TENSOR_MAP_SWIZZLE_128B);
    enc2(fn, &P.hg, d_in[7], 1792, 512, 32, 32, CU_TENSOR_MAP_SWIZZLE_NONE);
    enc2(fn, &P.hu, d_in[8], 1792, 512, 32, 32, CU_TENSOR_MAP_SWIZZLE_NONE);
    enc2(fn, &P.hp, pwp, 64, 4096, 32, 32, CU_TENSOR_MAP_SWIZZLE_NONE);
    enc2(fn, &P.wd, d_in[9], 512, 1792, 64, 32, CU_TENSOR_MAP_SWIZZLE_128B);
    enc2(fn, &P.xn, pxn, 512, 2048, 64, 64, CU_TENSOR_MAP_SWIZZLE_128B);
    enc2(fn, &P.xr, pxn, 512, 2048, 64, 16, CU_TENSOR_MAP_SWIZZLE_128B);
    enc3(fn, &P.out, d_out, 512, 2048, 16, 1);
    cudaGetSymbolAddress((void**)&P.fp, g_f);
    enc3(fn, &P.f, P.fp, 3 * 512, 2048, 16, 1);
    int dev = 0, sms = 0;
    cudaGetDevice(&dev);
    cudaDeviceGetAttribute(&sms, cudaDevAttrMultiProcessorCount, dev);
    if (sms == 132) {
        cudaFuncSetAttribute(fused_kernel<true>, cudaFuncAttributeMaxDynamicSharedMemorySize, SMEM_BYTES);
        fused_kernel<true><<<132, 384, SMEM_BYTES>>>(P);
    } else {
        cudaFuncSetAttribute(fused_kernel<false>, cudaFuncAttributeMaxDynamicSharedMemorySize, SMEM_BYTES);
        fused_kernel<false><<<128, 384, SMEM_BYTES>>>(P);
    }
}
```
